```python
import torch

def _softmax(x, axis=-1):
    return torch.softmax(x, dim=axis)

def _gelu(x):
    return torch.nn.functional.gelu(x, approximate='tanh')

def _silu(x):
    return torch.nn.functional.silu(x)

def _sigmoid(x):
    return torch.sigmoid(x)

def _layernorm(x, axis=-1, eps=1e-05):
    m = x.mean(dim=axis, keepdim=True)
    v = x.var(dim=axis, keepdim=True, unbiased=False)
    return (x - m) / torch.sqrt(v + eps)

def _scatter_add(tgt, idx, src, axis=0):
    return tgt.clone().index_add_(axis, idx, src)

def _segment_sum(src, seg, n):
    out = torch.zeros((n,) + src.shape[1:], dtype=src.dtype)
    return out.index_add_(0, seg, src)

def _pad(x, pw):
    flat = tuple((v for pair in reversed(pw) for v in pair))
    return torch.nn.functional.pad(x, flat)
kernel_name = 'adaLN_cond__ssm_conv_s4d__glu_gated_glu__prompt'

def setup_inputs():

    _w = lambda a: (lambda t: t.to(torch.bfloat16) if t.is_floating_point() else t)(torch.as_tensor(a))

    def _A_setup():
        Bsz, L, D, N = (1, 2048, 640, 192)
        return {'u': _w((lambda *s: torch.randn(*s, dtype=torch.bfloat16) * 0.05)(Bsz, L, D)), 'log_A_real': _w((lambda *s: torch.randn(*s, dtype=torch.bfloat16) * 3.2)(D, N) * 0.5), 'A_imag': _w((lambda *s: torch.randn(*s, dtype=torch.bfloat16) * 0.1)(D, N) * 3.14), 'C_real': _w((lambda *s: torch.randn(*s, dtype=torch.bfloat16) * 0.4)(D, N) / N ** 0.5), 'C_imag': _w((lambda *s: torch.randn(*s, dtype=torch.bfloat16) * 0.4)(D, N) / N ** 0.5), 'log_dt': _w((lambda *s: torch.randn(*s, dtype=torch.bfloat16) * 0.1)(D) * 0.5 - 4.0), 'D_skip': _w((lambda *s: torch.randn(*s, dtype=torch.bfloat16) * 0.1)(D))}
    _A_in = _A_setup()

    def _B_setup():
        B, S, D, F = (1, 2048, 640, 1536)
        return {'x': _w((lambda *s: torch.randn(*s, dtype=torch.bfloat16) * 0.05)(B, S, D)), 'w_gate': _w((lambda *s: torch.randn(*s, dtype=torch.bfloat16) * 0.05)(D, F)), 'w_up': _w((lambda *s: torch.randn(*s, dtype=torch.bfloat16) * 0.05)(D, F)), 'w_down': _w((lambda *s: torch.randn(*s, dtype=torch.bfloat16) * 0.05)(F, D))}
    _B_in = _B_setup()
    return {'A_u': _A_in['u'], 'A_log_A_real': _A_in['log_A_real'], 'A_A_imag': _A_in['A_imag'], 'A_C_real': _A_in['C_real'], 'A_C_imag': _A_in['C_imag'], 'A_log_dt': _A_in['log_dt'], 'A_D_skip': _A_in['D_skip'], 'B_x': _B_in['x'], 'B_w_gate': _B_in['w_gate'], 'B_w_up': _B_in['w_up'], 'B_w_down': _B_in['w_down'], 'c': _w((lambda *s: torch.randn(*s, dtype=torch.bfloat16) * 0.1)(1, 640) * 8.0), 'w_mod': _w((lambda *s: torch.randn(*s, dtype=torch.bfloat16) * 0.1)(640, 6 * 640) * 640 ** (-0.5) * 8.0)}

def reference(A_u, A_log_A_real, A_A_imag, A_C_real, A_C_imag, A_log_dt, A_D_skip, B_x, B_w_gate, B_w_up, B_w_down, c, w_mod):

    def _A_ref(u, log_A_real, A_imag, C_real, C_imag, log_dt, D_skip):
        L = u.shape[1]
        dt = torch.exp(log_dt)
        A = -torch.exp(log_A_real) + 1j * A_imag
        C = (C_real + 1j * C_imag) * dt[:, None]
        pos = (lambda x, dt: x.to(dt))(torch.arange(L), log_dt.dtype)
        P = torch.exp((A * dt[:, None])[:, :, None] * pos[None, None, :])
        K = 2.0 * torch.einsum('dn,dnl->dl', C, P).real
        L2 = 2 * L
        u_t = (lambda x, *d: x.permute(*d))(u, 0, 2, 1)
        Kf = (lambda x, *a, **k: torch.fft.rfft(x.float(), *a, **k))(K, L2)
        Uf = (lambda x, *a, **k: torch.fft.rfft(x.float(), *a, **k))(u_t, L2)
        y = (lambda x, *a, **k: torch.fft.irfft(x, *a, **k).to(torch.bfloat16))(Uf * Kf[None, :, :], L2)[:, :, :L]
        y = (lambda x, *d: x.permute(*d))(y, 0, 2, 1)
        return y + u * D_skip[None, None, :]

    def _B_ref(x, w_gate, w_up, w_down):
        g = torch.einsum('bsd,df->bsf', x, w_gate)
        u = torch.einsum('bsd,df->bsf', x, w_up)
        h = _sigmoid(g) * u
        return torch.einsum('bsf,fd->bsd', h, w_down)
    x = A_u
    mod = (_silu(c) @ w_mod).reshape(c.shape[0], 6, 1, -1)
    sa, ca, ga, sb, cb, gb = (mod[:, 0].clone(), mod[:, 1].clone(), mod[:, 2].clone(), mod[:, 3].clone(), mod[:, 4].clone(), mod[:, 5].clone())
    h = _layernorm(x, axis=-1) * (1 + ca) + sa
    x = x + ga * _A_ref(h, A_log_A_real, A_A_imag, A_C_real, A_C_imag, A_log_dt, A_D_skip)
    h = _layernorm(x, axis=-1) * (1 + cb) + sb
    x = x + gb * _B_ref(h, B_w_gate, B_w_up, B_w_down)
    return x
```

```cpp
#include <cuda_runtime.h>
#include <cuda_bf16.h>
#include <cuda_fp16.h>
#include <cuda.h>
#include <stdint.h>
#include <stdio.h>

constexpr int L_ = 2048;
constexpr int D_ = 640;
constexpr int NM_ = 192;
constexpr int F_ = 1536;

__device__ __forceinline__ uint32_t smem_u32(const void* p) { return (uint32_t)__cvta_generic_to_shared(p); }
__device__ __forceinline__ void mbar_init(uint32_t bar, uint32_t cnt) {
  asm volatile("mbarrier.init.shared::cta.b64 [%0], %1;" ::"r"(bar), "r"(cnt) : "memory");
}
__device__ __forceinline__ void mbar_expect_tx(uint32_t bar, uint32_t bytes) {
  asm volatile("mbarrier.arrive.expect_tx.shared::cta.b64 _, [%0], %1;" ::"r"(bar), "r"(bytes) : "memory");
}
__device__ __forceinline__ void mbar_arrive(uint32_t bar) {
  asm volatile("mbarrier.arrive.shared::cta.b64 _, [%0];" ::"r"(bar) : "memory");
}
__device__ __forceinline__ void mbar_arrive_remote(uint32_t cluster_bar) {
  asm volatile("mbarrier.arrive.relaxed.cluster.shared::cluster.b64 _, [%0];" ::"r"(cluster_bar) : "memory");
}
__device__ __forceinline__ void mbar_wait(uint32_t bar, uint32_t parity) {
  asm volatile("{\n.reg .pred p;\n.reg .u32 n;\nmov.u32 n, 1048576;\nW%=:\n"
               "mbarrier.try_wait.parity.shared::cta.b64 p, [%0], %1, 1000;\n@p bra.uni D%=;\n"
               "sub.u32 n, n, 1;\nsetp.ne.u32 p, n, 0;\n@p bra.uni W%=;\nD%=:\n}" ::"r"(bar), "r"(parity) : "memory");
}
__device__ __forceinline__ uint32_t mbar_test(uint32_t bar, uint32_t parity) {
  uint32_t ok;
  asm volatile("{\n.reg .pred p;\nmbarrier.test_wait.parity.shared::cta.b64 p, [%1], %2;\nselp.u32 %0, 1, 0, p;\n}"
               : "=r"(ok) : "r"(bar), "r"(parity) : "memory");
  return ok;
}
template <int NS>
__device__ __forceinline__ void mbar_wait_idle(uint32_t bar, uint32_t parity) {
  asm volatile("{\n.reg .pred p;\n.reg .u32 n;\nmov.u32 n, 4194304;\nW%=:\n"
               "mbarrier.test_wait.parity.shared::cta.b64 p, [%0], %1;\n@p bra.uni D%=;\nnanosleep.u32 %2;\n"
               "sub.u32 n, n, 1;\nsetp.ne.u32 p, n, 0;\n@p bra.uni W%=;\nD%=:\n}" ::"r"(bar), "r"(parity), "n"(NS) : "memory");
}
__device__ __forceinline__ void mbar_wait_cluster(uint32_t bar, uint32_t parity) {
  asm volatile("{\n.reg .pred p;\n.reg .u32 n;\nmov.u32 n, 1048576;\nW%=:\n"
               "mbarrier.try_wait.parity.acquire.cluster.shared::cta.b64 p, [%0], %1, 1000;\n@p bra.uni D%=;\n"
               "sub.u32 n, n, 1;\nsetp.ne.u32 p, n, 0;\n@p bra.uni W%=;\nD%=:\n}" ::"r"(bar), "r"(parity) : "memory");
}
__device__ __forceinline__ uint32_t mapa_u32(uint32_t addr, uint32_t rank) {
  uint32_t r;
  asm volatile("mapa.shared::cluster.u32 %0, %1, %2;" : "=r"(r) : "r"(addr), "r"(rank));
  return r;
}
__device__ __forceinline__ void tma_load_2d(uint32_t dst, const CUtensorMap* m, int c0, int c1, uint32_t bar) {
  asm volatile("cp.async.bulk.tensor.2d.shared::cluster.global.mbarrier::complete_tx::bytes [%0], [%1, {%3, %4}], [%2];"
               ::"r"(dst), "l"((uint64_t)m), "r"(bar), "r"(c0), "r"(c1) : "memory");
}
__device__ __forceinline__ void tma_load_3d(uint32_t dst, const CUtensorMap* m, int c0, int c1, int c2, uint32_t bar) {
  asm volatile("cp.async.bulk.tensor.3d.shared::cluster.global.mbarrier::complete_tx::bytes [%0], [%1, {%3, %4, %5}], [%2];"
               ::"r"(dst), "l"((uint64_t)m), "r"(bar), "r"(c0), "r"(c1), "r"(c2) : "memory");
}
__device__ __forceinline__ void tma_load_4d(uint32_t dst, const CUtensorMap* m, int c0, int c1, int c2, int c3, uint32_t bar) {
  asm volatile("cp.async.bulk.tensor.4d.shared::cluster.global.mbarrier::complete_tx::bytes [%0], [%1, {%3, %4, %5, %6}], [%2];"
               ::"r"(dst), "l"((uint64_t)m), "r"(bar), "r"(c0), "r"(c1), "r"(c2), "r"(c3) : "memory");
}
__device__ __forceinline__ void tma_store_2d(const CUtensorMap* m, uint32_t src, int c0, int c1) {
  asm volatile("cp.async.bulk.tensor.2d.global.shared::cta.bulk_group [%0, {%2, %3}], [%1];"
               ::"l"((uint64_t)m), "r"(src), "r"(c0), "r"(c1) : "memory");
}
__device__ __forceinline__ void tma_store_3d(const CUtensorMap* m, uint32_t src, int c0, int c1, int c2) {
  asm volatile("cp.async.bulk.tensor.3d.global.shared::cta.bulk_group [%0, {%2, %3, %4}], [%1];"
               ::"l"((uint64_t)m), "r"(src), "r"(c0), "r"(c1), "r"(c2) : "memory");
}
__device__ __forceinline__ void bulk_load(uint32_t dst, const void* src, uint32_t bytes, uint32_t bar) {
  asm volatile("cp.async.bulk.shared::cluster.global.mbarrier::complete_tx::bytes [%0], [%1], %2, [%3];"
               ::"r"(dst), "l"(src), "r"(bytes), "r"(bar) : "memory");
}
__device__ __forceinline__ void bulk_copy_peer(uint32_t dst_cluster, uint32_t src, uint32_t bytes, uint32_t bar_cluster) {
  asm volatile("cp.async.bulk.shared::cluster.shared::cta.mbarrier::complete_tx::bytes [%0], [%1], %2, [%3];"
               ::"r"(dst_cluster), "r"(src), "r"(bytes), "r"(bar_cluster) : "memory");
}
__device__ __forceinline__ void bulk_store(void* dst, uint32_t src, uint32_t bytes) {
  asm volatile("cp.async.bulk.global.shared::cta.bulk_group [%0], [%1], %2;" ::"l"(dst), "r"(src), "r"(bytes) : "memory");
}
__device__ __forceinline__ void bulk_commit() { asm volatile("cp.async.bulk.commit_group;" ::: "memory"); }
__device__ __forceinline__ void bulk_wait_all() { asm volatile("cp.async.bulk.wait_group 0;" ::: "memory"); }
__device__ __forceinline__ void bulk_wait_read() { asm volatile("cp.async.bulk.wait_group.read 0;" ::: "memory"); }
__device__ __forceinline__ void fence_async_smem() { asm volatile("fence.proxy.async.shared::cta;" ::: "memory"); }
__device__ __forceinline__ void fence_async_all() { asm volatile("fence.proxy.async;" ::: "memory"); }
__device__ __forceinline__ void prefetch_tmap(const CUtensorMap* m) {
  asm volatile("prefetch.tensormap [%0];" ::"l"((uint64_t)m) : "memory");
}
__device__ __forceinline__ void wg_fence() { asm volatile("wgmma.fence.sync.aligned;" ::: "memory"); }
__device__ __forceinline__ void wg_commit() { asm volatile("wgmma.commit_group.sync.aligned;" ::: "memory"); }
template <int N> __device__ __forceinline__ void wg_wait() { asm volatile("wgmma.wait_group.sync.aligned %0;" ::"n"(N) : "memory"); }
__device__ __forceinline__ uint64_t make_desc(uint32_t addr, uint32_t lbo, uint32_t sbo, uint32_t swz) {
  return (uint64_t)((addr & 0x3FFFF) >> 4) | ((uint64_t)(lbo >> 4) << 16) | ((uint64_t)(sbo >> 4) << 32) | ((uint64_t)swz << 62);
}
__device__ __forceinline__ void ldsm_x4(uint32_t addr, uint32_t& r0, uint32_t& r1, uint32_t& r2, uint32_t& r3) {
  asm volatile("ldmatrix.sync.aligned.m8n8.x4.shared.b16 {%0,%1,%2,%3}, [%4];"
               : "=r"(r0), "=r"(r1), "=r"(r2), "=r"(r3) : "r"(addr) : "memory");
}
__device__ __forceinline__ void ldsm_x4_t(uint32_t addr, uint32_t& r0, uint32_t& r1, uint32_t& r2, uint32_t& r3) {
  asm volatile("ldmatrix.sync.aligned.m8n8.x4.trans.shared.b16 {%0,%1,%2,%3}, [%4];"
               : "=r"(r0), "=r"(r1), "=r"(r2), "=r"(r3) : "r"(addr) : "memory");
}
__device__ __forceinline__ void stsm_x4(uint32_t addr, uint32_t r0, uint32_t r1, uint32_t r2, uint32_t r3) {
  asm volatile("stmatrix.sync.aligned.m8n8.x4.shared.b16 [%0], {%1,%2,%3,%4};"
               ::"r"(addr), "r"(r0), "r"(r1), "r"(r2), "r"(r3) : "memory");
}
__device__ __forceinline__ void stsm_x4_t(uint32_t addr, uint32_t r0, uint32_t r1, uint32_t r2, uint32_t r3) {
  asm volatile("stmatrix.sync.aligned.m8n8.x4.trans.shared.b16 [%0], {%1,%2,%3,%4};"
               ::"r"(addr), "r"(r0), "r"(r1), "r"(r2), "r"(r3) : "memory");
}
__device__ __forceinline__ void stsm_x4_nc(uint32_t addr, uint32_t r0, uint32_t r1, uint32_t r2, uint32_t r3) {
  asm volatile("stmatrix.sync.aligned.m8n8.x4.shared.b16 [%0], {%1,%2,%3,%4};"
               ::"r"(addr), "r"(r0), "r"(r1), "r"(r2), "r"(r3));
}
__device__ __forceinline__ float4 lds128f_nv(uint32_t a) {
  float4 r;
  asm("ld.shared.v4.f32 {%0,%1,%2,%3}, [%4];" : "=f"(r.x), "=f"(r.y), "=f"(r.z), "=f"(r.w) : "r"(a));
  return r;
}
__device__ __forceinline__ uint32_t opaque(uint32_t v) {
  asm volatile("mov.b32 %0, %0;" : "+r"(v) :: "memory");
  return v;
}
__device__ __forceinline__ uint32_t pack_bf16(float lo, float hi) {
  uint32_t r;
  asm("cvt.rn.bf16x2.f32 %0, %1, %2;" : "=r"(r) : "f"(hi), "f"(lo));
  return r;
}
__device__ __forceinline__ float bf_lo(uint32_t v) { return __uint_as_float(v << 16); }
__device__ __forceinline__ float bf_hi(uint32_t v) { return __uint_as_float(v & 0xffff0000u); }
__device__ __forceinline__ float bf_round(float x) { return __bfloat162float(__float2bfloat16_rn(x)); }
__device__ __forceinline__ uint32_t hmul2_bf16(uint32_t a, uint32_t b) {
  uint32_t r;
  asm("mul.rn.bf16x2 %0, %1, %2;" : "=r"(r) : "r"(a), "r"(b));
  return r;
}
__device__ __forceinline__ uint32_t hadd2_bf16(uint32_t a, uint32_t b) {
  uint32_t r;
  asm("add.rn.bf16x2 %0, %1, %2;" : "=r"(r) : "r"(a), "r"(b));
  return r;
}
__device__ __forceinline__ float ex2_approx(float x) {
  float r;
  asm("ex2.approx.ftz.f32 %0, %1;" : "=f"(r) : "f"(x));
  return r;
}
__device__ __forceinline__ float rcp_approx(float x) {
  float r;
  asm("rcp.approx.ftz.f32 %0, %1;" : "=f"(r) : "f"(x));
  return r;
}
__device__ __forceinline__ float sqrt_approx(float x) {
  float r;
  asm("sqrt.approx.ftz.f32 %0, %1;" : "=f"(r) : "f"(x));
  return r;
}
__device__ __forceinline__ float tanh_approx(float x) {
  float r;
  asm("tanh.approx.f32 %0, %1;" : "=f"(r) : "f"(x));
  return r;
}
__device__ __forceinline__ uint32_t lds32(uint32_t a) {
  uint32_t r;
  asm volatile("ld.shared.b32 %0, [%1];" : "=r"(r) : "r"(a));
  return r;
}
__device__ __forceinline__ float4 lds128f(uint32_t a) {
  float4 r;
  asm volatile("ld.shared.v4.f32 {%0,%1,%2,%3}, [%4];" : "=f"(r.x), "=f"(r.y), "=f"(r.z), "=f"(r.w) : "r"(a));
  return r;
}
__device__ __forceinline__ void named_bar_sync(int id, int n) { asm volatile("bar.sync %0, %1;" ::"r"(id), "r"(n) : "memory"); }
__device__ __forceinline__ void pdl_wait() { asm volatile("griddepcontrol.wait;" ::: "memory"); }
__device__ __forceinline__ void pdl_launch() { asm volatile("griddepcontrol.launch_dependents;" ::: "memory"); }
__device__ __forceinline__ uint32_t ld_acquire(const uint32_t* p) {
  uint32_t v;
  asm volatile("ld.acquire.gpu.global.u32 %0, [%1];" : "=r"(v) : "l"(p) : "memory");
  return v;
}
__device__ __forceinline__ void red_release_add(uint32_t* p, uint32_t v) {
  asm volatile("red.release.gpu.global.add.u32 [%0], %1;" ::"l"(p), "r"(v) : "memory");
}
__device__ __forceinline__ void st_release(uint32_t* p, uint32_t v) {
  asm volatile("st.release.gpu.global.u32 [%0], %1;" ::"l"(p), "r"(v) : "memory");
}
__device__ __forceinline__ uint32_t ld_relaxed(const uint32_t* p) {
  uint32_t v;
  asm volatile("ld.relaxed.gpu.global.u32 %0, [%1];" : "=r"(v) : "l"(p) : "memory");
  return v;
}
__device__ __forceinline__ void st_relaxed(uint32_t* p, uint32_t v) {
  asm volatile("st.relaxed.gpu.global.u32 [%0], %1;" ::"l"(p), "r"(v) : "memory");
}
__device__ __forceinline__ void red_relaxed_inc(uint32_t* p) {
  asm volatile("red.relaxed.gpu.global.add.u32 [%0], 1;" ::"l"(p) : "memory");
}
#define TL(k)
#define TLM(k)
#define TLC(k)
#define TLG(k)
#define TL0(k)
#define TL_DUMP(lo, hi)
__device__ __forceinline__ void wgmma_rs_n128(float (&d)[64], uint32_t a0, uint32_t a1, uint32_t a2, uint32_t a3, uint64_t db, int scale_d) {
  asm volatile("{\n.reg .pred p;\nsetp.ne.b32 p, %69, 0;\n"
    "wgmma.mma_async.sync.aligned.m64n128k16.f32.bf16.bf16 {%0,%1,%2,%3,%4,%5,%6,%7,%8,%9,%10,%11,%12,%13,%14,%15,%16,%17,%18,%19,%20,%21,%22,%23,%24,%25,%26,%27,%28,%29,%30,%31,%32,%33,%34,%35,%36,%37,%38,%39,%40,%41,%42,%43,%44,%45,%46,%47,%48,%49,%50,%51,%52,%53,%54,%55,%56,%57,%58,%59,%60,%61,%62,%63}, {%64,%65,%66,%67}, %68, p, 1, 1, 1;\n}\n"
    : "+f"(d[0]),"+f"(d[1]),"+f"(d[2]),"+f"(d[3]),"+f"(d[4]),"+f"(d[5]),"+f"(d[6]),"+f"(d[7]),"+f"(d[8]),"+f"(d[9]),"+f"(d[10]),"+f"(d[11]),"+f"(d[12]),"+f"(d[13]),"+f"(d[14]),"+f"(d[15]),"+f"(d[16]),"+f"(d[17]),"+f"(d[18]),"+f"(d[19]),"+f"(d[20]),"+f"(d[21]),"+f"(d[22]),"+f"(d[23]),"+f"(d[24]),"+f"(d[25]),"+f"(d[26]),"+f"(d[27]),"+f"(d[28]),"+f"(d[29]),"+f"(d[30]),"+f"(d[31]),"+f"(d[32]),"+f"(d[33]),"+f"(d[34]),"+f"(d[35]),"+f"(d[36]),"+f"(d[37]),"+f"(d[38]),"+f"(d[39]),"+f"(d[40]),"+f"(d[41]),"+f"(d[42]),"+f"(d[43]),"+f"(d[44]),"+f"(d[45]),"+f"(d[46]),"+f"(d[47]),"+f"(d[48]),"+f"(d[49]),"+f"(d[50]),"+f"(d[51]),"+f"(d[52]),"+f"(d[53]),"+f"(d[54]),"+f"(d[55]),"+f"(d[56]),"+f"(d[57]),"+f"(d[58]),"+f"(d[59]),"+f"(d[60]),"+f"(d[61]),"+f"(d[62]),"+f"(d[63])
    : "r"(a0), "r"(a1), "r"(a2), "r"(a3), "l"(db), "r"(scale_d));
}

__device__ __forceinline__ void wgmma_ss_n128t(float (&d)[64], uint64_t da, uint64_t db, int scale_d) {
  asm volatile("{\n.reg .pred p;\nsetp.ne.b32 p, %66, 0;\n"
    "wgmma.mma_async.sync.aligned.m64n128k16.f32.bf16.bf16 {%0,%1,%2,%3,%4,%5,%6,%7,%8,%9,%10,%11,%12,%13,%14,%15,%16,%17,%18,%19,%20,%21,%22,%23,%24,%25,%26,%27,%28,%29,%30,%31,%32,%33,%34,%35,%36,%37,%38,%39,%40,%41,%42,%43,%44,%45,%46,%47,%48,%49,%50,%51,%52,%53,%54,%55,%56,%57,%58,%59,%60,%61,%62,%63}, %64, %65, p, 1, 1, 1, 1;\n}\n"
    : "+f"(d[0]),"+f"(d[1]),"+f"(d[2]),"+f"(d[3]),"+f"(d[4]),"+f"(d[5]),"+f"(d[6]),"+f"(d[7]),"+f"(d[8]),"+f"(d[9]),"+f"(d[10]),"+f"(d[11]),"+f"(d[12]),"+f"(d[13]),"+f"(d[14]),"+f"(d[15]),"+f"(d[16]),"+f"(d[17]),"+f"(d[18]),"+f"(d[19]),"+f"(d[20]),"+f"(d[21]),"+f"(d[22]),"+f"(d[23]),"+f"(d[24]),"+f"(d[25]),"+f"(d[26]),"+f"(d[27]),"+f"(d[28]),"+f"(d[29]),"+f"(d[30]),"+f"(d[31]),"+f"(d[32]),"+f"(d[33]),"+f"(d[34]),"+f"(d[35]),"+f"(d[36]),"+f"(d[37]),"+f"(d[38]),"+f"(d[39]),"+f"(d[40]),"+f"(d[41]),"+f"(d[42]),"+f"(d[43]),"+f"(d[44]),"+f"(d[45]),"+f"(d[46]),"+f"(d[47]),"+f"(d[48]),"+f"(d[49]),"+f"(d[50]),"+f"(d[51]),"+f"(d[52]),"+f"(d[53]),"+f"(d[54]),"+f"(d[55]),"+f"(d[56]),"+f"(d[57]),"+f"(d[58]),"+f"(d[59]),"+f"(d[60]),"+f"(d[61]),"+f"(d[62]),"+f"(d[63])
    : "l"(da), "l"(db), "r"(scale_d));
}

__device__ __forceinline__ void wgmma_ss_n160(float (&d)[80], uint64_t da, uint64_t db, int scale_d) {
  asm volatile("{\n.reg .pred p;\nsetp.ne.b32 p, %82, 0;\n"
    "wgmma.mma_async.sync.aligned.m64n160k16.f32.bf16.bf16 {%0,%1,%2,%3,%4,%5,%6,%7,%8,%9,%10,%11,%12,%13,%14,%15,%16,%17,%18,%19,%20,%21,%22,%23,%24,%25,%26,%27,%28,%29,%30,%31,%32,%33,%34,%35,%36,%37,%38,%39,%40,%41,%42,%43,%44,%45,%46,%47,%48,%49,%50,%51,%52,%53,%54,%55,%56,%57,%58,%59,%60,%61,%62,%63,%64,%65,%66,%67,%68,%69,%70,%71,%72,%73,%74,%75,%76,%77,%78,%79}, %80, %81, p, 1, 1, 0, 1;\n}\n"
    : "+f"(d[0]),"+f"(d[1]),"+f"(d[2]),"+f"(d[3]),"+f"(d[4]),"+f"(d[5]),"+f"(d[6]),"+f"(d[7]),"+f"(d[8]),"+f"(d[9]),"+f"(d[10]),"+f"(d[11]),"+f"(d[12]),"+f"(d[13]),"+f"(d[14]),"+f"(d[15]),"+f"(d[16]),"+f"(d[17]),"+f"(d[18]),"+f"(d[19]),"+f"(d[20]),"+f"(d[21]),"+f"(d[22]),"+f"(d[23]),"+f"(d[24]),"+f"(d[25]),"+f"(d[26]),"+f"(d[27]),"+f"(d[28]),"+f"(d[29]),"+f"(d[30]),"+f"(d[31]),"+f"(d[32]),"+f"(d[33]),"+f"(d[34]),"+f"(d[35]),"+f"(d[36]),"+f"(d[37]),"+f"(d[38]),"+f"(d[39]),"+f"(d[40]),"+f"(d[41]),"+f"(d[42]),"+f"(d[43]),"+f"(d[44]),"+f"(d[45]),"+f"(d[46]),"+f"(d[47]),"+f"(d[48]),"+f"(d[49]),"+f"(d[50]),"+f"(d[51]),"+f"(d[52]),"+f"(d[53]),"+f"(d[54]),"+f"(d[55]),"+f"(d[56]),"+f"(d[57]),"+f"(d[58]),"+f"(d[59]),"+f"(d[60]),"+f"(d[61]),"+f"(d[62]),"+f"(d[63]),"+f"(d[64]),"+f"(d[65]),"+f"(d[66]),"+f"(d[67]),"+f"(d[68]),"+f"(d[69]),"+f"(d[70]),"+f"(d[71]),"+f"(d[72]),"+f"(d[73]),"+f"(d[74]),"+f"(d[75]),"+f"(d[76]),"+f"(d[77]),"+f"(d[78]),"+f"(d[79])
    : "l"(da), "l"(db), "r"(scale_d));
}

__device__ __align__(1024) __nv_bfloat16 g_xT[D_ * L_];
__device__ __align__(1024) __nv_bfloat16 g_x1T[D_ * L_];
__device__ __align__(1024) __nv_bfloat16 g_wdt[F_ * D_];
__device__ __align__(1024) __nv_bfloat16 g_hh[L_ * F_];

struct __align__(128) Sync {
  uint32_t stat[L_];
  uint32_t modp[4][6 * D_];
  uint2 vw[2][F_];
  uint32_t hhflag[384][8];
  uint32_t cnt[32][8];
};
__device__ Sync g_sync[2];
__device__ uint32_t g_epoch;

constexpr int NS1 = 5, SLOT1 = 32768;
constexpr int NB2 = 7, SB2 = 20480;
constexpr int SA2 = 16384;
constexpr int OFF_STG = NS1 * SLOT1;
constexpr int OFF_A2 = OFF_STG - SA2;
constexpr int OFF_RES = 5 * SB2, OFF_RECV = 6 * SB2, OFF_OUT = 0;
constexpr int OFF_C1 = OFF_STG + 3 * 16384;
constexpr int OFF_VW = 219136;
constexpr int OFF_GB = OFF_C1 + 4352;
constexpr int OFF_BAR = OFF_GB + 640;
constexpr int OFF_ZERO = OFF_BAR + 1008, OFF_TILE = OFF_BAR + 1012, OFF_PAR = OFF_BAR + 1016;
constexpr int OFF_TO = 16384;
constexpr int OFF_WC = OFF_TO + 20480;
constexpr int OFF_WB0 = 0, OFF_WB1 = OFF_C1;
constexpr int OFF_W = OFF_TO;
constexpr int PRMW = 6656;
constexpr int OFF_PRM = OFF_W + 40960;
constexpr int OFF_Z2 = 3 * SLOT1;
constexpr int OFF_Z3 = OFF_Z2 + 33280;
constexpr int TABW = 736;
constexpr int OFF_TAB2 = OFF_PRM + 15 * PRMW;
constexpr int OFF_TAB1 = OFF_BAR + 1024;
constexpr int XP = 4096;
constexpr int OFF_X1 = OFF_STG, OFF_XR = OFF_STG;
constexpr int HP = 140;
constexpr int OFF_H = OFF_X1 + 20480, OFF_TI = OFF_H;
constexpr int OFF_VEC = OFF_H + 22400;
constexpr int OFF_SM = OFF_VEC + 2560;
constexpr int OFF_CV = OFF_SM + 128;
constexpr int OFF_BOXC = OFF_CV + 384;
constexpr int SMEM = OFF_TAB1 + 3 * TABW * 4 + 1024;
static_assert(OFF_Z3 + 25600 <= OFF_TAB2 && OFF_TAB2 + 2 * TABW * 4 <= OFF_STG && OFF_BOXC + 2048 <= OFF_C1 && SMEM <= 231424 && OFF_WB1 % 1024 == 0 &&
              OFF_VW >= OFF_TAB1 && OFF_VW + 6144 + 1024 <= SMEM, "layout");
__device__ __forceinline__ uint32_t tab_off(int ch) { return (ch < 3 ? OFF_TAB1 : OFF_TAB2 - 3 * TABW * 4) + ch * TABW * 4; }

enum : int {
  B_TI, B_X, B_WC, B_WB, B_EP, B_S, B_TO, B_W, B_XC, B_SC, B_CD, B_PB, B_BOX, B_UNIT = B_BOX + 5, B_TILE = B_UNIT + 5,
  B_WFREE, B_CONV, B_VW, B_FULL1, B_EMPTY1 = B_FULL1 + 5,
  B_FULLB = B_EMPTY1 + 5, B_FULLA = B_FULLB + 12, B_DRAIN = B_FULLA + 18, B_STG = B_DRAIN + 16, B_HOLD = B_STG + 6,
  B_RES = B_HOLD + 2, B_PEER, B_RECV, B_PRM, B_WD, B_WV, NBAR = B_WV + 2
};
__host__ __device__ constexpr int bar_count(int i) {
  return i == B_S ? 2 : i == B_TO ? 10 : i == B_WFREE ? 5 : i == B_CONV ? 10 : i == B_VW ? 11
       : (i >= B_FULL1 && i < B_EMPTY1) ? 2 : (i >= B_EMPTY1 && i < B_FULLB) ? 8
       : (i >= B_DRAIN && i < B_STG) ? (((i - B_DRAIN) & 7) < 3 ? 5 : 4) : (i >= B_STG && i < B_HOLD) ? 4 : i == B_RES ? 2 : 1;
}
static_assert(NBAR * 8 <= 1008, "barrier block");
#define X4MASK 0
#define VWSPLIT 0x5310
#define BOX2W 9
#define SIDEBAR B_BOX
#define W4BAR (B_WV + 1)
#define W5BAR B_BOX
#define W6BAR B_BOX
#define BOXMAP 0xFFFF2F0F4FFF3FFFull
#define RARE(c) __builtin_expect(!!(c), 0)
#define HOLD_Q 1
#define RSIDE "104"
#define RCONV "136"
#define KU_ 2
constexpr int KU = KU_;
#define SKEW 3

__device__ __forceinline__ void mma_bf16(float& d0, float& d1, float& d2, float& d3, uint32_t a0, uint32_t a1, uint32_t a2,
                                         uint32_t a3, uint32_t b0, uint32_t b1) {
  asm volatile("mma.sync.aligned.m16n8k16.row.col.f32.bf16.bf16.f32 {%0,%1,%2,%3},{%4,%5,%6,%7},{%8,%9},{%0,%1,%2,%3};"
               : "+f"(d0), "+f"(d1), "+f"(d2), "+f"(d3) : "r"(a0), "r"(a1), "r"(a2), "r"(a3), "r"(b0), "r"(b1));
}
__device__ __forceinline__ void mma_f16(float (&d)[4], uint32_t a0, uint32_t a1, uint32_t a2, uint32_t a3, uint32_t b0, uint32_t b1) {
  asm volatile("mma.sync.aligned.m16n8k16.row.col.f32.f16.f16.f32 {%0,%1,%2,%3},{%4,%5,%6,%7},{%8,%9},{%0,%1,%2,%3};"
               : "+f"(d[0]), "+f"(d[1]), "+f"(d[2]), "+f"(d[3]) : "r"(a0), "r"(a1), "r"(a2), "r"(a3), "r"(b0), "r"(b1));
}
__device__ __forceinline__ uint32_t h2u(__half2 h) { return *reinterpret_cast<uint32_t*>(&h); }
__device__ __forceinline__ __half2 u2h(uint32_t u) { return *reinterpret_cast<__half2*>(&u); }
__device__ __forceinline__ void cexp_p(float a, float b, float p, float& re, float& im) {
  float m = ex2_approx(a * p), ang = b * p;
  re = m * __cosf(ang);
  im = m * __sinf(ang);
}
__device__ __forceinline__ void csq(float& r, float& i) {
  const float t = r + r;
  r = fmaf(r, r, -i * i);
  i *= t;
}
__device__ __forceinline__ void cmul_h2(__half2 xr, __half2 xi, __half2 yr, __half2 yi, __half2& zr, __half2& zi) {
  zr = __hfma2(__hneg2(xi), yi, __hmul2(xr, yr));
  zi = __hfma2(xi, yr, __hmul2(xr, yi));
}
__device__ __forceinline__ uint4 lds128(uint32_t a) {
  uint4 r;
  asm volatile("ld.shared.v4.u32 {%0,%1,%2,%3}, [%4];" : "=r"(r.x), "=r"(r.y), "=r"(r.z), "=r"(r.w) : "r"(a));
  return r;
}
__device__ __forceinline__ void sts128(uint32_t a, uint4 v) {
  asm volatile("st.shared.v4.u32 [%0], {%1,%2,%3,%4};" ::"r"(a), "r"(v.x), "r"(v.y), "r"(v.z), "r"(v.w) : "memory");
}
__device__ __forceinline__ void sts64(uint32_t a, uint32_t x, uint32_t y) {
  asm volatile("st.shared.v2.u32 [%0], {%1,%2};" ::"r"(a), "r"(x), "r"(y) : "memory");
}
__device__ __forceinline__ void sts32(uint32_t a, uint32_t x) { asm volatile("st.shared.b32 [%0], %1;" ::"r"(a), "r"(x) : "memory"); }
__device__ __forceinline__ float ldsf(uint32_t a) { return __uint_as_float(lds32(a)); }
__device__ __forceinline__ void prefetch_l2(const void* p, uint32_t bytes) {
  asm volatile("cp.async.bulk.prefetch.L2.global [%0], %1;" ::"l"(p), "r"(bytes) : "memory");
}

__device__ __forceinline__ uint32_t ldg32v(const void* p) {
  uint32_t r;
  asm volatile("ld.global.nc.b32 %0, [%1];" : "=r"(r) : "l"(p));
  return r;
}
__device__ __forceinline__ uint32_t ldg16v(const void* p) {
  uint16_t r;
  asm volatile("ld.global.nc.u16 %0, [%1];" : "=h"(r) : "l"(p));
  return r;
}
__device__ __forceinline__ uint2 ldg64v(const void* p) {
  uint2 r;
  asm volatile("ld.global.nc.v2.b32 {%0,%1}, [%2];" : "=r"(r.x), "=r"(r.y) : "l"(p));
  return r;
}
__device__ __forceinline__ uint4 ldg128v(const void* p) {
  uint4 r;
  asm volatile("ld.global.nc.L1::no_allocate.v4.b32 {%0,%1,%2,%3}, [%4];" : "=r"(r.x), "=r"(r.y), "=r"(r.z), "=r"(r.w) : "l"(p));
  return r;
}
__device__ __forceinline__ uint4 ld_relaxed128(const void* p) {
  uint4 r;
  asm volatile("ld.relaxed.gpu.global.v4.b32 {%0,%1,%2,%3}, [%4];" : "=r"(r.x), "=r"(r.y), "=r"(r.z), "=r"(r.w) : "l"(p) : "memory");
  return r;
}
__device__ __forceinline__ uint32_t lds32v(uint32_t a) {
  uint32_t r;
  asm volatile("ld.volatile.shared.b32 %0, [%1];" : "=r"(r) : "r"(a));
  return r;
}
__device__ __forceinline__ uint2 lds64(uint32_t a) {
  uint2 r;
  asm volatile("ld.shared.v2.u32 {%0,%1}, [%2];" : "=r"(r.x), "=r"(r.y) : "r"(a));
  return r;
}
__device__ __forceinline__ void ldsm_x2(uint32_t addr, uint32_t& r0, uint32_t& r1) {
  asm volatile("ldmatrix.sync.aligned.m8n8.x2.shared.b16 {%0,%1}, [%2];" : "=r"(r0), "=r"(r1) : "r"(addr));
}
__device__ __forceinline__ void ldsm_x4_t_nc(uint32_t addr, uint32_t& r0, uint32_t& r1, uint32_t& r2, uint32_t& r3) {
  asm volatile("ldmatrix.sync.aligned.m8n8.x4.trans.shared.b16 {%0,%1,%2,%3}, [%4];"
               : "=r"(r0), "=r"(r1), "=r"(r2), "=r"(r3) : "r"(addr));
}
__device__ __forceinline__ void ldsm_x4_nc(uint32_t addr, uint32_t& r0, uint32_t& r1, uint32_t& r2, uint32_t& r3) {
  asm volatile("ldmatrix.sync.aligned.m8n8.x4.shared.b16 {%0,%1,%2,%3}, [%4];"
               : "=r"(r0), "=r"(r1), "=r"(r2), "=r"(r3) : "r"(addr));
}
__device__ __forceinline__ uint32_t hfma2_bf16(uint32_t a, uint32_t b, uint32_t c) {
  uint32_t r;
  asm("fma.rn.bf16x2 %0, %1, %2, %3;" : "=r"(r) : "r"(a), "r"(b), "r"(c));
  return r;
}
__device__ __forceinline__ void cmulf(float xr, float xi, float yr, float yi, float& zr, float& zi) {
  zr = fmaf(xr, yr, -xi * yi);
  zi = fmaf(xr, yi, xi * yr);
}
__device__ __forceinline__ uint32_t pack_h2(float lo, float hi) { return h2u(__floats2half2_rn(lo, hi)); }

__device__ __forceinline__ void conv_half(uint32_t sb, int ch, int H, int lane, int bidx) {
  const int g = lane >> 2, t4 = lane & 3, lr = lane & 7, lm = lane >> 3;
  const uint32_t tab = sb + tab_off(ch);
  float acc[8][4];
#pragma unroll
  for (int i = 0; i < 8; i++)
#pragma unroll
    for (int j = 0; j < 4; j++) acc[i][j] = 0.f;
  const uint32_t h4a = sb + OFF_H + (ch * 2 * HP + 8 + H * 64 + lr + ((lm == 0) ? HP - 1 : (lm == 3) ? HP : 0)) * 16;
  {
    uint32_t kb[66];
#pragma unroll
    for (int u = 0; u < 66; u++) kb[u ^ 1] = lds32(tab + (7 + 8 * u + g - 2 * t4) * 4);
    const uint32_t zero = (uint32_t)bidx >> 16;
    uint32_t pv[3], dummy;
    ldsm_x2(h4a + 57 * 16, pv[0], dummy);
    ldsm_x2(h4a + 25 * 16, pv[1], dummy);
#pragma unroll
    for (int s = 0; s < 32; s++) {
#pragma unroll
      for (int st = 0; st < 2; st++) {
        const int xx = 112 - 2 * s - 64 * st;
        uint32_t q0, q1, q2, q3;
        if ((X4MASK >> st) & 1) {
          ldsm_x4_nc(h4a + (xx / 2) * 16, q0, q1, q2, q3);
        } else {
          ldsm_x2(h4a + (xx / 2) * 16, q0, q1);
          q2 = q1 ^ zero; q3 = pv[st] ^ zero;
        }
        pv[st] = q0;
#pragma unroll
        for (int i = 0; i < 8; i++) {
          const int J = (16 * i - xx) / 2;
          if (J >= 0 && J <= 32) mma_bf16(acc[i][0], acc[i][1], acc[i][2], acc[i][3], q0, q1, q2, q3, kb[2 * J], kb[2 * J + 1]);
        }
      }
    }
    if (ch == 0 && lane == 0) mbar_arrive(sb + OFF_BAR + 8 * (B_WV + H));
    if (H) {
      float tmp[3][4];
#pragma unroll
      for (int i = 0; i < 3; i++)
#pragma unroll
        for (int j = 0; j < 4; j++) tmp[i][j] = 0.f;
#pragma unroll
      for (int u = 16; u < 66; u++) kb[u ^ 1] = lds32v(tab + (7 + 8 * u + g - 2 * t4) * 4);
      pv[0] = pv[1];
      ldsm_x2(h4a + (-32 / 2) * 16, pv[1], dummy);
      ldsm_x2(h4a + (-48 / 2) * 16, pv[2], dummy);
      const uint32_t kk = lds32(tab + 728 * 4);
      const int dd = g - 2 * t4;
      const uint32_t b128 = ((dd == 3 || dd == 4) ? (kk & 0xffffu) : 0u) | ((dd == 4 || dd == 5) ? (kk & 0xffff0000u) : 0u);
      const uint32_t b129 = ((dd == -5 || dd == -4) ? (kk & 0xffffu) : 0u) | ((dd == -4 || dd == -3) ? (kk & 0xffff0000u) : 0u);
#pragma unroll
      for (int s = 0; s < 9; s++) {
#pragma unroll
        for (int st = 0; st < 3; st++) {
          if (st > 0 && s == 0) continue;
          const int xx = -16 - 2 * s - 16 * st;
          uint32_t q0, q1, q2, q3;
          if ((X4MASK >> 2) & 1) {
            ldsm_x4_nc(h4a + (xx / 2) * 16, q0, q1, q2, q3);
          } else {
            ldsm_x2(h4a + (xx / 2) * 16, q0, q1);
            q2 = q1 ^ zero; q3 = pv[st] ^ zero;
          }
          pv[st] = q0;
#pragma unroll
          for (int i = 0; i < 4; i++) {
            const int J = (16 * i - xx) / 2;
            if (J <= 32) {
              float(&d)[4] = st == 0 ? acc[i] : st == 1 ? tmp[i] : tmp[2];
              mma_bf16(d[0], d[1], d[2], d[3], q0, q1, q2, q3, kb[2 * J], kb[2 * J + 1]);
            }
          }
        }
        if (s > 0) {
          uint32_t f0, f1, f2, f3;
          ldsm_x4_nc(h4a + (8 * (8 - s) - 64) * 16, f0, f1, f2, f3);
          mma_bf16(acc[8 - s][0], acc[8 - s][1], acc[8 - s][2], acc[8 - s][3], f0, f1, f2, f3, b129, b128);
        }
      }
#pragma unroll
      for (int j = 0; j < 4; j++) { acc[0][j] += tmp[0][j] + tmp[2][j]; acc[1][j] += tmp[1][j]; }
    }
  }
  {
    uint32_t ka[5][8];
#pragma unroll
    for (int d = 0; d < 5; d++) {
      const uint32_t a = tab + (536 + 16 + 16 * d + 2 * g - 4 * t4) * 4;
      ka[d][0] = lds32v(a); ka[d][1] = lds32v(a + 4); ka[d][2] = lds32v(a - 4); ka[d][3] = lds32v(a);
      ka[d][4] = lds32v(a - 8); ka[d][5] = lds32v(a - 4); ka[d][6] = lds32v(a - 12); ka[d][7] = lds32v(a - 8);
    }
    mbar_wait(sb + OFF_BAR + 8 * (B_BOX + ch), 0);
    const uint32_t zb = sb + OFF_Z2 + ((ch * 8 + g) * 208 + H * 128 + 4 * t4) * 4;
#pragma unroll
    for (int y = 3; y >= -8; y--) {
      if (y == -1 && !H) break;
      const uint4 z = lds128(zb + y * 64);
#pragma unroll
      for (int i = 0; i < 8; i++) {
        const int d = i - 4 - y;
        if (d >= 0 && d < 5) mma_bf16(acc[i][0], acc[i][1], acc[i][2], acc[i][3], ka[d][0], ka[d][1], ka[d][2], ka[d][3], z.x, z.y);
      }
#pragma unroll
      for (int i = 0; i < 8; i++) {
        const int d = i - 4 - y;
        if (d >= 0 && d < 5) mma_bf16(acc[i][0], acc[i][1], acc[i][2], acc[i][3], ka[d][4], ka[d][5], ka[d][6], ka[d][7], z.z, z.w);
      }
    }
  }
  if (H) {
    uint32_t ka[4][8];
#pragma unroll
    for (int d = 0; d < 4; d++)
#pragma unroll
      for (int o = 0; o < 8; o++) ka[d][o] = lds32(tab + (632 + 16 + 16 * d + g - 4 * t4 + (o & 1) * 8 - (o >> 1)) * 4);
    float a3[4][2][4];
#pragma unroll
    for (int q = 0; q < 4; q++)
#pragma unroll
      for (int p = 0; p < 2; p++)
#pragma unroll
        for (int j = 0; j < 4; j++) a3[q][p][j] = 0.f;
    const uint32_t zb = sb + OFF_Z3 + ((ch * 16 + g) * 80 + 4 * t4) * 4;
#pragma unroll
    for (int y = 0; y < 4; y++) {
      const uint4 z0 = lds128(zb + y * 64), z1 = lds128(zb + 8 * 80 * 4 + y * 64);
#pragma unroll
      for (int q = y; q < 4; q++) {
        mma_bf16(a3[q][0][0], a3[q][0][1], a3[q][0][2], a3[q][0][3], ka[q - y][0], ka[q - y][1], ka[q - y][2], ka[q - y][3], z0.x, z0.y);
        mma_bf16(a3[q][1][0], a3[q][1][1], a3[q][1][2], a3[q][1][3], ka[q - y][0], ka[q - y][1], ka[q - y][2], ka[q - y][3], z1.x, z1.y);
      }
#pragma unroll
      for (int q = y; q < 4; q++) {
        mma_bf16(a3[q][0][0], a3[q][0][1], a3[q][0][2], a3[q][0][3], ka[q - y][4], ka[q - y][5], ka[q - y][6], ka[q - y][7], z0.z, z0.w);
        mma_bf16(a3[q][1][0], a3[q][1][1], a3[q][1][2], a3[q][1][3], ka[q - y][4], ka[q - y][5], ka[q - y][6], ka[q - y][7], z1.z, z1.w);
      }
    }
#pragma unroll
    for (int q = 0; q < 4; q++)
#pragma unroll
      for (int p = 0; p < 2; p++) {
        acc[2 * q][2 * p] += a3[q][p][0]; acc[2 * q][2 * p + 1] += a3[q][p][1];
        acc[2 * q + 1][2 * p] += a3[q][p][2]; acc[2 * q + 1][2 * p + 1] += a3[q][p][3];
      }
  }
  __syncwarp();
  if (lane == 0) mbar_arrive(sb + OFF_BAR + 8 * B_CONV);
  {
    const uint32_t xa = sb + OFF_X1 + ch * XP + H * 2048 + (lm >> 1) * 256 + lr * 32 + (lm & 1) * 16;
    uint32_t xv[16];
#pragma unroll
    for (int i = 0; i < 4; i++) ldsm_x4_nc(xa + i * 512, xv[4 * i], xv[4 * i + 1], xv[4 * i + 2], xv[4 * i + 3]);
    const uint32_t ga2 = lds32(sb + OFF_SM + ch * 16 + 8);
#pragma unroll
    for (int i = 0; i < 8; i++) {
      xv[2 * i] = hfma2_bf16(ga2, pack_bf16(acc[i][0], acc[i][1]), xv[2 * i]);
      xv[2 * i + 1] = hfma2_bf16(ga2, pack_bf16(acc[i][2], acc[i][3]), xv[2 * i + 1]);
    }
#pragma unroll
    for (int i = 0; i < 4; i++) stsm_x4(xa + i * 512, xv[4 * i], xv[4 * i + 1], xv[4 * i + 2], xv[4 * i + 3]);
    fence_async_smem();
    __syncwarp();
  }
}

__device__ __forceinline__ void gemv64x160(uint32_t w0, uint32_t w1, int lane, uint32_t vec, uint32_t* dst) {
  const int lr = lane & 7, lm = lane >> 3;
  float acc[4][4];
  const uint32_t ro = ((lm >> 1) * 8 + lr) * 128;
  const uint32_t x0 = ro + (((lm & 1) ^ lr) << 4);
#pragma unroll 1
  for (int hf = 0; hf < 2; hf++) {
    uint32_t a[20][4], bb[20];
#pragma unroll
    for (int k = 0; k < 5; k++) ldsm_x4_nc(vec + lm * 16 + k * 64, bb[4 * k], bb[4 * k + 1], bb[4 * k + 2], bb[4 * k + 3]);
    const uint32_t xa = x0 ^ (hf << 6), xb = xa ^ 32;
#pragma unroll
    for (int k = 0; k < 10; k++) {
      const uint32_t wa = k < 8 ? w0 + k * 2048 : w1 + (k - 8) * 2048;
      ldsm_x4_t_nc(wa + xa, a[2 * k][0], a[2 * k][1], a[2 * k][2], a[2 * k][3]);
      ldsm_x4_t_nc(wa + xb, a[2 * k + 1][0], a[2 * k + 1][1], a[2 * k + 1][2], a[2 * k + 1][3]);
    }
#pragma unroll
    for (int i = 0; i < 4; i++)
#pragma unroll
      for (int j = 0; j < 4; j++) acc[i][j] = 0.f;
#pragma unroll
    for (int j = 0; j < 20; j++)
      mma_bf16(acc[j & 3][0], acc[j & 3][1], acc[j & 3][2], acc[j & 3][3], a[j][0], a[j][1], a[j][2], a[j][3], bb[j & 30], bb[(j & 30) + 1]);
    if ((lane & 3) == 0) {
      st_relaxed(dst + hf * 32, __float_as_uint(acc[0][0] + acc[2][0]) | 1u);
      st_relaxed(dst + hf * 32 + 8, __float_as_uint(acc[0][2] + acc[2][2]) | 1u);
      st_relaxed(dst + hf * 32 + 16, __float_as_uint(acc[1][0] + acc[3][0]) | 1u);
      st_relaxed(dst + hf * 32 + 24, __float_as_uint(acc[1][2] + acc[3][2]) | 1u);
    }
    __syncwarp();
  }
}

__device__ __forceinline__ void row_stats(uint32_t rows, int lane, uint32_t bar_s, uint32_t* dst) {
  const int lr = lane & 7, lm = lane >> 3;
  const uint32_t base = rows + lr * 1280 + (lm & 1) * 640;
  float s[2][4], p[2][4], q[2][4];
#pragma unroll
  for (int i = 0; i < 2; i++)
#pragma unroll
    for (int j = 0; j < 4; j++) s[i][j] = p[i][j] = q[i][j] = 0.f;
#pragma unroll 1
  for (int k0 = 0; k0 < 5; k0++) {
    uint32_t a[4][4], c[4][4];
#pragma unroll
    for (int k = 0; k < 4; k++) {
      ldsm_x4_nc(base + k0 * 128 + (((2 * k + (lm >> 1)) ^ lr) << 4), a[k][0], a[k][1], a[k][2], a[k][3]);
      ldsm_x4_nc(rows + lr * 1280 + (lm >> 1) * 640 + k0 * 128 + (((2 * k + (lm & 1)) ^ lr) << 4), c[k][0], c[k][1], c[k][2], c[k][3]);
    }
#pragma unroll
    for (int k = 0; k < 4; k++) {
      mma_bf16(s[k & 1][0], s[k & 1][1], s[k & 1][2], s[k & 1][3], a[k][0], a[k][1], a[k][2], a[k][3], 0x3f803f80u, 0x3f803f80u);
      mma_bf16(p[k & 1][0], p[k & 1][1], p[k & 1][2], p[k & 1][3], a[k][0], a[k][1], a[k][2], a[k][3], c[k][0], c[k][1]);
      mma_bf16(q[k & 1][0], q[k & 1][1], q[k & 1][2], q[k & 1][3], a[k][0], a[k][1], a[k][2], a[k][3], c[k][2], c[k][3]);
    }
  }
  __syncwarp();
  if (lane == 0) mbar_arrive(bar_s);
  const bool odd = (lane >> 2) & 1;
  const float mean = ((s[0][0] + s[1][0]) + (s[0][2] + s[1][2])) * (1.f / D_);
  const float sq = odd ? (p[0][1] + p[1][1]) + (q[0][3] + q[1][3]) : (p[0][0] + p[1][0]) + (q[0][2] + q[1][2]);
  const float var = fmaxf(fmaf(-mean, mean, sq * (1.f / D_)), 0.f);
  const uint32_t word = pack_bf16(mean, sqrt_approx(bf_round(bf_round(var) + 1e-5f)));
  if ((lane & 3) == (lane >> 3)) st_relaxed(dst + (lane >> 2), word);
}

__device__ __forceinline__ float sum4_bf(uint32_t a, uint32_t b, uint32_t c, uint32_t d) {
  return bf_round((__uint_as_float(a) + __uint_as_float(b)) + (__uint_as_float(c) + __uint_as_float(d)));
}
__device__ __forceinline__ float poll_mod(const uint32_t* p) {
  uint32_t w0 = 0, w1 = 0, w2 = 0, w3 = 0;
#pragma unroll 1
  for (int it = 0; it < (1 << 20) && !__all_sync(~0u, (w0 & w1 & w2 & w3 & 1u) != 0); it++) {
    w0 = ld_relaxed(p); w1 = ld_relaxed(p + 6 * D_); w2 = ld_relaxed(p + 12 * D_); w3 = ld_relaxed(p + 18 * D_);
  }
  return sum4_bf(w0, w1, w2, w3);
}
__device__ __forceinline__ uint32_t silu2(uint32_t c) {
  const float c0 = bf_lo(c), c1 = bf_hi(c);
  return pack_bf16(c0 * rcp_approx(1.f + ex2_approx(-1.4426950408889634f * c0)),
                   c1 * rcp_approx(1.f + ex2_approx(-1.4426950408889634f * c1)));
}

__device__ __forceinline__ uint32_t box_w(int lag, int lo, int hi) {
  return ((lag >= lo && lag <= hi) ? 0x3f80u : 0u) | ((lag - 1 >= lo && lag - 1 <= hi) ? 0x3f800000u : 0u);
}
__device__ __forceinline__ void box_setup(uint32_t sb, int lane) {
  const int g = lane >> 2, t4 = lane & 3;
#pragma unroll 1
  for (int a = 0; a < 2; a++) {
    const int lag = 4 * a + (g >> 1) - 2 * t4;
    const int lo2 = (g & 1) ? 3 : 0, hi2 = (g & 1) ? 7 : 2, lo3 = (g & 1) ? 7 : 0, hi3 = (g & 1) ? 15 : 6;
    const int n2 = 4 * a + t4 + 3, n3 = n2 + 2;
    sts128(sb + OFF_BOXC + a * 1024 + lane * 16,
           make_uint4(box_w(lag + 8, lo2, hi2), box_w(lag, lo2, hi2), box_w(lag + 8, lo3, hi3), box_w(lag, lo3, hi3)));
    sts128(sb + OFF_BOXC + a * 1024 + 512 + lane * 16,
           make_uint4(OFF_Z2 + ((n2 & 7) * 208 + 2 * g + (n2 >> 3)) * 4, box_w(lag + 16, lo3, hi3), OFF_Z3 + (n3 * 80 + g) * 4,
                      OFF_Z3 + (((n3 + 8) & 15) * 80 + g + ((n3 + 8) >> 4)) * 4));
  }
}
__device__ __forceinline__ void box_sums(uint32_t sb, int ch, int lane) {
  const int lr = lane & 7, lm = lane >> 3;
  uint32_t w2[2][2], w3[2][3], o2[2], o3[2][2];
#pragma unroll
  for (int a = 0; a < 2; a++) {
    const uint4 c0 = lds128(sb + OFF_BOXC + a * 1024 + lane * 16), c1 = lds128(sb + OFF_BOXC + a * 1024 + 512 + lane * 16);
    w2[a][0] = c0.x; w2[a][1] = c0.y; w3[a][0] = c0.z; w3[a][1] = c0.w;
    o2[a] = c1.x; w3[a][2] = c1.y; o3[a][0] = c1.z; o3[a][1] = c1.w;
  }
  {
    const uint32_t ha = sb + OFF_H + (ch * 2 * HP + 8 + lr + ((lm == 0) ? HP - 1 : (lm == 3) ? HP : 0)) * 16;
    const uint32_t z2 = sb + ch * (8 * 208 * 4), z3 = sb + ch * (16 * 80 * 4);
    if (lane < 3) sts32(z2 + OFF_Z2 + lane * 208 * 4, 0u);
    if (lane < 5) sts32(z3 + OFF_Z3 + lane * 80 * 4, 0u);
#pragma unroll 1
    for (int i0 = 0; i0 < 12; i0 += 4) {
      uint32_t q[4][4];
      float d[4][2][4];
#pragma unroll
      for (int i = 0; i < 4; i++) ldsm_x4_nc(ha + (i0 + i) * 128, q[i][0], q[i][1], q[i][2], q[i][3]);
#pragma unroll
      for (int i = 0; i < 4; i++)
#pragma unroll
        for (int a = 0; a < 2; a++) {
          d[i][a][0] = d[i][a][1] = d[i][a][2] = d[i][a][3] = 0.f;
          mma_bf16(d[i][a][0], d[i][a][1], d[i][a][2], d[i][a][3], q[i][0], q[i][1], q[i][2], q[i][3], w2[a][0], w2[a][1]);
        }
      if (i0 < 8) {
        uint32_t p[4][4];
        float e[4][2][4];
#pragma unroll
        for (int i = 0; i < 4; i++) ldsm_x4_nc(ha + (i0 + i) * 128 - 16, p[i][0], p[i][1], p[i][2], p[i][3]);
#pragma unroll
        for (int i = 0; i < 4; i++)
#pragma unroll
          for (int a = 0; a < 2; a++) {
            e[i][a][0] = e[i][a][1] = e[i][a][2] = e[i][a][3] = 0.f;
            mma_bf16(e[i][a][0], e[i][a][1], e[i][a][2], e[i][a][3], q[i][0], q[i][1], q[i][2], q[i][3], w3[a][0], w3[a][1]);
          }
#pragma unroll
        for (int i = 0; i < 4; i++)
#pragma unroll
          for (int a = 0; a < 2; a++)
            mma_bf16(e[i][a][0], e[i][a][1], e[i][a][2], e[i][a][3], p[i][0], p[i][1], p[i][2], p[i][3], 0u, w3[a][2]);
#pragma unroll
        for (int i = 0; i < 4; i++)
#pragma unroll
          for (int a = 0; a < 2; a++) {
            sts32(z3 + o3[a][0] + (i0 + i) * 32, pack_bf16(e[i][a][0], e[i][a][1]));
            sts32(z3 + o3[a][1] + (i0 + i) * 32, pack_bf16(e[i][a][2], e[i][a][3]));
          }
      }
#pragma unroll
      for (int i = 0; i < 4; i++)
#pragma unroll
        for (int a = 0; a < 2; a++) {
          sts32(z2 + o2[a] + (i0 + i) * 64, pack_bf16(d[i][a][0], d[i][a][1]));
          sts32(z2 + o2[a] + (i0 + i) * 64 + 4, pack_bf16(d[i][a][2], d[i][a][3]));
        }
    }
    __syncwarp();
    if (lane == 0) { mbar_arrive(sb + OFF_BAR + 8 * (B_BOX + ch)); TLM(118 + ch); }
  }
}

__device__ __forceinline__ void k2_stats(uint32_t r, float& s1, float& s2) {
  float lo = bf_lo(r), hi = bf_hi(r);
  s1 += lo; s2 = fmaf(lo, lo, s2);
  s1 += hi; s2 = fmaf(hi, hi, s2);
}

template <int HF>
__device__ __forceinline__ void k2_glu_half(const float (&acc)[64], uint32_t stg, float rh0, float rh1) {
  uint32_t h[8];
#pragma unroll
  for (int jj = 0; jj < 4; jj++) {
    const int j = 4 * HF + jj;
    const float e00 = tanh_approx(rh0 * acc[4 * j + 0]), e01 = tanh_approx(rh0 * acc[4 * j + 1]);
    const float e10 = tanh_approx(rh1 * acc[4 * j + 2]), e11 = tanh_approx(rh1 * acc[4 * j + 3]);
    const float u00 = rh0 * acc[32 + 4 * j + 0], u01 = rh0 * acc[32 + 4 * j + 1];
    const float u10 = rh1 * acc[32 + 4 * j + 2], u11 = rh1 * acc[32 + 4 * j + 3];
    h[2 * jj + 0] = pack_bf16(fmaf(u00, e00, u00), fmaf(u01, e01, u01));
    h[2 * jj + 1] = pack_bf16(fmaf(u10, e10, u10), fmaf(u11, e11, u11));
  }
#pragma unroll
  for (int q = 0; q < 2; q++) stsm_x4_nc(stg ^ ((4 * HF + 2 * q) << 4), h[4 * q], h[4 * q + 1], h[4 * q + 2], h[4 * q + 3]);
}

__device__ __forceinline__ void publish_x1(uint32_t sb, Sync* sy, int b, int ch, int H, int lane) {
  if (lane == 0) {
    bulk_store(g_x1T + (size_t)(ch * 128 + b) * L_ + H * 1024, sb + OFF_X1 + ch * XP + H * 2048, 2048);
    bulk_commit();
  }
  __syncwarp();
  bulk_wait_all();
  if (lane == 0) {
    red_relaxed_inc(&sy->cnt[16 + 8 * H + ch][0]);
    mbar_arrive(sb + OFF_BAR + 8 * B_VW);
  }
  __syncwarp();
}

struct Maps { CUtensorMap xi, xo, wma, wmb, wgc, wuc, x1, res, wg, wu, wd, out; };

__global__ void __cluster_dims__(2, 1, 1) __launch_bounds__(512, 1)
fused_kernel(const __nv_bfloat16* __restrict__ x, const __nv_bfloat16* __restrict__ lar, const __nv_bfloat16* __restrict__ aim,
             const __nv_bfloat16* __restrict__ cre, const __nv_bfloat16* __restrict__ cim, const __nv_bfloat16* __restrict__ ldt,
             const __nv_bfloat16* __restrict__ dsk, const __nv_bfloat16* __restrict__ cvec,
             const __grid_constant__ Maps tm) {
  extern __shared__ uint8_t smem_raw[];
  const uint32_t sb = (smem_u32(smem_raw) + 1023u) & ~1023u;
  const int tid = threadIdx.x, lane = tid & 31, b = blockIdx.x;
  const int warp = __shfl_sync(~0u, tid >> 5, 0);
  const int g = lane >> 2, t4 = lane & 3;
  const int rank = b & 1;
  const int rg = min(b / 30, 3), cgp = b - rg * 30;
  auto bar = [&](int i) { return sb + OFF_BAR + 8 * i; };
  if (tid == 0) { TL0(0); TL0(24); }
  TLC(0);

  if (warp == 15) {
    if (lane == 0) {
#pragma unroll
      for (int i = 0; i < B_BOX; i++) mbar_init(bar(i), bar_count(i));
      sts32(sb + OFF_ZERO, 0u);
      asm volatile("fence.mbarrier_init.release.cluster;" ::: "memory");
    }
    __syncwarp();
    asm volatile("bar.arrive 1, 512;" ::: "memory");
    asm volatile("barrier.cluster.arrive.relaxed.aligned;" ::: "memory");
    const uint32_t epoch = ld_relaxed(&g_epoch);
    if (lane == 0) {
      mbar_expect_tx(bar(B_TI), 20480);
      tma_load_3d(sb + OFF_TI, &tm.xi, 0, (b >> 2) * 64, (b & 3) * 5, bar(B_TI));
      mbar_expect_tx(bar(B_X), 20480);
      bulk_load(sb + OFF_XR, x + (size_t)b * 16 * D_, 20480, bar(B_X));
      prefetch_tmap(&tm.wma); prefetch_tmap(&tm.wmb); prefetch_tmap(&tm.xo);
      sts32(sb + OFF_PAR, epoch & 1);
      mbar_arrive(bar(B_EP));
      TL(4);
      if (b < 120) {
        mbar_expect_tx(bar(B_WC), 20480);
        tma_load_2d(sb + OFF_WC, &tm.wma, cgp * 64, rg * 160, bar(B_WC));
        tma_load_2d(sb + OFF_WC + 16384, &tm.wmb, cgp * 64, rg * 160 + 128, bar(B_WC));
      }
    }
    __syncwarp();
    Sync* sy = &g_sync[epoch & 1];
    uint32_t xf = ld_relaxed(&sy->cnt[12 + (b >> 5)][0]);
    mbar_wait(bar(B_TI), 0);
    if (lane == 0 && b < 120) {
      mbar_expect_tx(bar(B_WB), 20480);
      tma_load_2d(sb + OFF_WB0, &tm.wma, 3 * D_ + cgp * 64, rg * 160, bar(B_WB));
      tma_load_2d(sb + OFF_WB1, &tm.wmb, 3 * D_ + cgp * 64, rg * 160 + 128, bar(B_WB));
    }
    __syncwarp();
    mbar_wait(bar(B_TO), 0);
    if (lane == 0) {
      TL(14);
      tma_store_2d(&tm.xo, sb + OFF_TO, (b >> 2) * 64, (b & 3) * 160);
      bulk_commit();
    }
    __syncwarp();
    bulk_wait_all();
    if (lane == 0) {
      red_relaxed_inc(&sy->cnt[12 + (b & 3)][0]);
      TL(18);
    }
    mbar_wait(bar(B_S), 0);
    {
      const int sec = min(lane / 5, 2), pc = min(lane - sec * 5, 4);
      const uint32_t* p = &sy->modp[0][sec * D_ + b * 5 + pc];
      uint32_t w0 = 0, w1 = 0, w2 = 0, w3 = 0;
      bool xdone = false;
#pragma unroll 1
      for (int it = 0; it < (1 << 20); it++) {
        if (!xdone && __all_sync(~0u, xf >= 32u)) {
          xdone = true;
          if (lane == 0) {
            TL(19);
            mbar_expect_tx(bar(B_XC), 20480);
            bulk_load(sb + OFF_X1, g_xT + (size_t)(b * 5) * L_, 20480, bar(B_XC));
          }
          __syncwarp();
        }
        if (xdone && __all_sync(~0u, (w0 & w1 & w2 & w3 & 1u) != 0)) break;
        xf = ld_relaxed(&sy->cnt[12 + (b >> 5)][0]);
        w0 = ld_relaxed(p); w1 = ld_relaxed(p + 6 * D_); w2 = ld_relaxed(p + 12 * D_); w3 = ld_relaxed(p + 18 * D_);
      }
      const float v = sum4_bf(w0, w1, w2, w3) + (sec == 1 ? 1.f : 0.f);
      if (lane < 15) sts32(sb + OFF_SM + (pc * 4 + sec) * 4, pack_bf16(v, v));
      __syncwarp();
      if (lane == 0) { mbar_arrive(bar(B_SC)); TL(21); }
    }
    mbar_wait(bar(B_CD), 0);
    if (lane == 0 && b < 96) {
      mbar_expect_tx(bar(B_W), 40960);
#pragma unroll 1
      for (int i = 0; i < 4; i++)
        tma_load_2d(sb + OFF_W + i * 10240, b < 48 ? &tm.wgc : &tm.wuc, (b < 48 ? b : b - 48) * 32, i * 160, bar(B_W));
    }
    __syncwarp();
    if (b < 120) {
      mbar_wait(bar(B_WB), 0);
      gemv64x160(sb + OFF_WB0, sb + OFF_WB1, lane, sb + OFF_CV, &sy->modp[rg][3 * D_ + cgp * 64 + g]);
    }
    if (lane == 0) TL(34);
  } else {
    const int po = b * (5 * NM_ / 2) + tid;
    uint32_t p_lar = ldg32v((const uint32_t*)lar + po), p_aim = ldg32v((const uint32_t*)aim + po);
    uint32_t p_cre = ldg32v((const uint32_t*)cre + po), p_cim = ldg32v((const uint32_t*)cim + po);
    uint32_t p_ldt = ldg16v(ldt + b * 5 + warp / 3), p_dsk = ldg16v(dsk + b * 5 + warp / 3);
    const uint2 cq = ldg64v(cvec + rg * 160 + lane * 4), cq2 = ldg64v(cvec + rg * 160 + 128 + (lane & 7) * 4);
    if (RARE(warp < 4)) {
      Sync* z = &g_sync[warp & 1];
      uint4* p = warp < 2 ? (uint4*)&z->modp[rg][(lane >> 4) * 3 * D_ + cgp * 64] + (lane & 15)
               : lane < 16 ? (uint4*)&z->vw[0][b * 32] + lane
               : (uint4*)&z->stat[b * 16] + (lane & 3);
      if (warp < 2 ? b < 120 : (lane >= 16 || b < 96)) *p = make_uint4(0, 0, 0, 0);
    }
    if (warp != 13) asm volatile("barrier.cluster.arrive.relaxed.aligned;" ::: "memory");
    named_bar_sync(1, 512);
    if (RARE(warp == 14)) box_setup(sb, lane);
    {
      const uint32_t z = lds32v(sb + OFF_ZERO);
      p_lar ^= z; p_aim ^= z; p_cre ^= z; p_cim ^= z; p_ldt ^= z; p_dsk ^= z;
    }

    const uint32_t prm = sb + OFF_PRM + warp * PRMW;
    float kscale, k0part;
    {
      constexpr float L2E = 1.4426950408889634f;
      const float dt = bf_lo(pack_bf16(ex2_approx(bf_lo(p_ldt) * L2E), 0.f));
      const uint32_t ar2 = pack_bf16(ex2_approx(bf_lo(p_lar) * L2E), ex2_approx(bf_hi(p_lar) * L2E));
      const float a1 = -bf_lo(ar2) * dt * L2E, a2 = -bf_hi(ar2) * dt * L2E;
      const float b1 = bf_lo(p_aim) * dt, b2 = bf_hi(p_aim) * dt;
      const float cr1 = bf_lo(p_cre), cr2 = bf_hi(p_cre), ci1 = bf_lo(p_cim), ci2 = bf_hi(p_cim);
      uint32_t mx = __float_as_uint(fmaxf(fmaxf(fabsf(cr1), fabsf(cr2)), fmaxf(fabsf(ci1), fabsf(ci2))));
      mx = __reduce_max_sync(~0u, mx) & 0x7f800000u;
      const float s = __uint_as_float(0x7f000000u - mx);
      kscale = 2.f * dt * __uint_as_float(mx);
      k0part = cr1 + cr2;
#pragma unroll
      for (int o = 16; o; o >>= 1) k0part += __shfl_xor_sync(~0u, k0part, o);
      k0part *= 2.f * dt;
      if (warp % 3 == 0) k0part += bf_lo(p_dsk);
      if (tid == 0) TL(22);
      float e1r, e1i, f1r, f1i, e8r, e8i, f8r, f8i, ur, ui, vr, vi;
      cexp_p(a1, b1, 1.f, e1r, e1i);   cexp_p(a2, b2, 1.f, f1r, f1i);
      cexp_p(a1, b1, 8.f, e8r, e8i);   cexp_p(a2, b2, 8.f, f8r, f8i);
      cexp_p(a1, b1, 64.f, ur, ui);    cexp_p(a2, b2, 64.f, vr, vi);
      {
        const uint32_t ca = prm + 4096 + lane * 80;
        uint4 w;
        w.x = pack_h2(ur, vr); w.y = pack_h2(ui, vi);
        csq(ur, ui); csq(vr, vi);
        w.z = pack_h2(ur, vr); w.w = pack_h2(ui, vi);
        sts128(ca, w);
        float pr, pi, qr, qi;
        cmulf(ur, ui, e1r, e1i, pr, pi); cmulf(vr, vi, f1r, f1i, qr, qi);
#pragma unroll
        for (int k = 1; k < 4; k++) {
          w.x = pack_h2(pr, qr); w.y = pack_h2(pi, qi);
          csq(ur, ui); csq(vr, vi);
          w.z = pack_h2(ur, vr); w.w = pack_h2(ui, vi);
          sts128(ca + 16 * k, w);
          if (k < 3) { csq(pr, pi); csq(qr, qi); }
        }
      }
      {
        float br = 1.f, bi = 0.f, dr = 1.f, di = 0.f, ar, an, cr_, cn_;
        cmulf(cr1 * s, -ci1 * s, e1r, -e1i, ar, an);
        cmulf(cr2 * s, -ci2 * s, f1r, -f1i, cr_, cn_);
#pragma unroll
        for (int k = 0; k < 8; k++) {
          {
            const uint32_t ti = (g * 0x90 + t4 * 4) ^ (k << 4);
            sts64(prm + 2 * ti, pack_h2(br, dr), pack_h2(bi, di));
            sts32(prm + 2048 + ti, pack_h2(ar, cr_));
            sts32(prm + 3072 + ti, pack_h2(an, cn_));
          }
          if (k < 7) {
            if (k == 0) { br = e1r; bi = e1i; dr = f1r; di = f1i; }
            else { cmulf(br, bi, e1r, e1i, br, bi); cmulf(dr, di, f1r, f1i, dr, di); }
            cmulf(ar, an, e8r, -e8i, ar, an); cmulf(cr_, cn_, f8r, -f8i, cr_, cn_);
          }
        }
      }
    }
    if (tid == 0) TL(3);
    if (RARE(warp == 13)) {
      if (lane == 0) {
#pragma unroll
        for (int i = B_BOX; i < NBAR; i++)
          if (i < B_FULLB || i >= B_RES) mbar_init(bar(i), bar_count(i));
        mbar_expect_tx(bar(B_TILE), 4);
        mbar_expect_tx(bar(B_RECV), 20480);
        asm volatile("fence.mbarrier_init.release.cluster;" ::: "memory");
      }
      __syncwarp();
      asm volatile("barrier.cluster.arrive.relaxed.aligned;" ::: "memory");
    }
    const int tw = warp - (warp >> 2);
    if ((warp & 3) != 3 && tw < 10) {
      const int lr = lane & 7, lm = lane >> 3, cg = tw >> 1, i0 = (tw & 1) * 4;
      const uint32_t src = sb + OFF_TI + cg * 4096 + i0 * 512 + lr * 64 + ((lm ^ (lr >> 1)) << 4);
      const uint32_t dst = sb + OFF_TO + cg * 4096 + lane * 128;
      mbar_wait(bar(B_TI), 0);
      if (tid == 0) TL(17);
      uint4 v[4];
#pragma unroll
      for (int i = 0; i < 4; i++) ldsm_x4_t(src + i * 512, v[i].x, v[i].y, v[i].z, v[i].w);
#pragma unroll
      for (int i = 0; i < 4; i++) stsm_x4(dst + (((i0 + i) ^ lr) << 4), v[i].x, v[i].y, v[i].z, v[i].w);
      fence_async_smem();
      __syncwarp();
      if (lane == 0) mbar_arrive(bar(B_TO));
    }
    mbar_wait(bar(B_EP), 0);
    Sync* sy = &g_sync[lds32v(sb + OFF_PAR)];
    if (RARE(warp == 3 || warp == 7)) {
      mbar_wait(bar(B_X), 0);
      row_stats(sb + OFF_XR + (warp >> 2) * (8 * 1280), lane, bar(B_S), &sy->stat[b * 16 + (warp >> 2) * 8]);
      if (tid == 96) TL(2);
    }
    {
      float acc[5][4];
#pragma unroll
      for (int i = 0; i < 5; i++)
#pragma unroll
        for (int j = 0; j < 4; j++) acc[i][j] = 0.f;
      const uint32_t ca = prm + 4096 + t4 * 80;
      const uint32_t c1a = ca + 16 + (g & 1) * 8, c2a = ca + 32 + ((g >> 1) & 1) * 8, c3a = ca + 48 + (g >> 2) * 8;
      __syncwarp();
#pragma unroll 1
      for (int hf = 0; hf < 2; hf++) {
        if (RARE(warp == 11 && hf == 1)) {
          sts64(sb + OFF_CV + lane * 8, silu2(cq.x), silu2(cq.y));
          sts64(sb + OFF_CV + 256 + (lane & 7) * 8, silu2(cq2.x), silu2(cq2.y));
          __syncwarp();
          if (b < 120) {
            mbar_wait(bar(B_WC), 0);
            gemv64x160(sb + OFF_WC, sb + OFF_WC + 16384, lane, sb + OFF_CV, &sy->modp[rg][cgp * 64 + g]);
          }
          if (lane == 0) { mbar_arrive(bar(B_CD)); TL(5); }
        }
#pragma unroll KU
        for (int st = 4 * hf; st < 4 * hf + 4; st++) {
          const uint32_t ti = (lane * 4) ^ (st * 0x90);
          const uint2 b0 = lds64(prm + 2 * ti);
          const uint32_t f0 = lds32v(prm + 2048 + ti), f2 = lds32v(prm + 3072 + ti);
          const uint4 e = lds128(ca + st * 320);
          const uint2 v1 = lds64(c1a + st * 320), v2 = lds64(c2a + st * 320), v3 = lds64(c3a + st * 320);
          __half2 a1r, a1n, b1r, b1i, b2r, b2i, b3r, b3i, b4r, b4i;
          cmul_h2(u2h(f0), u2h(f2), u2h(e.x), __hneg2(u2h(e.y)), a1r, a1n);
          cmul_h2(u2h(b0.x), u2h(b0.y), u2h(e.z), u2h(e.w), b1r, b1i);
          cmul_h2(b1r, b1i, u2h(v1.x), u2h(v1.y), b2r, b2i);
          cmul_h2(b2r, b2i, u2h(v2.x), u2h(v2.y), b3r, b3i);
          cmul_h2(b3r, b3i, u2h(v3.x), u2h(v3.y), b4r, b4i);
          const uint32_t f1 = h2u(a1r), f3 = h2u(a1n);
          mma_f16(acc[0], f0, f1, f2, f3, b0.x, b0.y);
          mma_f16(acc[1], f0, f1, f2, f3, h2u(b1r), h2u(b1i));
          mma_f16(acc[2], f0, f1, f2, f3, h2u(b2r), h2u(b2i));
          mma_f16(acc[3], f0, f1, f2, f3, h2u(b3r), h2u(b3i));
          mma_f16(acc[4], f0, f1, f2, f3, h2u(b4r), h2u(b4i));
        }
      }
      __syncwarp();
      const uint32_t pp = prm + 16;
      const int c1 = t4 & 1, c2 = t4 >> 1;
#pragma unroll
      for (int hh = 0; hh < 2; hh++) {
        const int r = g + hh * 8;
        sts64(pp + (8 * r + 2 * t4) * 4, __float_as_uint(acc[0][2 * hh] * kscale), __float_as_uint(acc[0][2 * hh + 1] * kscale));
        sts64(pp + (128 + 8 * r + 2 * t4) * 4, __float_as_uint(acc[1][2 * hh] * kscale), __float_as_uint(acc[1][2 * hh + 1] * kscale));
#pragma unroll
        for (int c0 = 0; c0 < 2; c0++) {
          sts32(pp + (256 + 4 * r + 64 * c0 + t4) * 4, __float_as_uint(acc[2][2 * hh + c0] * kscale));
          sts32(pp + (384 + 2 * r + 32 * c0 + 64 * c1 + c2) * 4, __float_as_uint(acc[3][2 * hh + c0] * kscale));
          sts32(pp + (512 + r + 16 * c0 + 32 * c1 + 64 * c2) * 4, __float_as_uint(acc[4][2 * hh + c0] * kscale));
        }
      }
      if (lane == 0) sts32(pp - 4, __float_as_uint(k0part));
    }
    if (tid == 0) TL(6);
    const uint4 stw = ld_relaxed128(&sy->stat[tid * 4]), stx = ld_relaxed128(&sy->stat[(480 + lane) * 4]);
    named_bar_sync(3 + warp / 3, 96);
    if (tid == 0) TL(7);
    {
      const int ch = warp / 3, sub = warp - ch * 3;
      const uint32_t tab = sb + tab_off(ch);
      const uint32_t pp = sb + OFF_PRM + ch * (3 * PRMW);
      const uint32_t a = pp + 16 + ((sub == 0 ? 0 : sub == 1 ? 64 : 96) + lane) * 16;
      const uint32_t a2 = a + 512;
      const float4 u0 = lds128f(a), u1 = lds128f(a + PRMW), u2 = lds128f(a + 2 * PRMW);
      const float4 w0 = lds128f(a2), w1 = lds128f(a2 + PRMW), w2 = lds128f(a2 + 2 * PRMW);
      const uint32_t ea = lane == 0 ? a - 4 : pp + (lane == 1 ? 3 : lane == 2 ? 387 : 515) * 4;
      const float e = ldsf(ea) + ldsf(ea + PRMW) + ldsf(ea + 2 * PRMW);
      const float v1 = u0.x + u1.x + u2.x, v2 = u0.y + u1.y + u2.y, v3 = u0.z + u1.z + u2.z, v4 = u0.w + u1.w + u2.w;
      const float y1 = w0.x + w1.x + w2.x, y2 = w0.y + w1.y + w2.y, y3 = w0.z + w1.z + w2.z, y4 = w0.w + w1.w + w2.w;
      float p = __shfl_up_sync(~0u, v4, 1), q = __shfl_sync(~0u, lane == 31 ? v4 : y4, (lane + 31) & 31);
      if (lane == 0) p = e;
      if (sub == 0) {
        sts128(tab + (8 + lane * 4) * 4, make_uint4(pack_bf16(v1, p), pack_bf16(v2, v1), pack_bf16(v3, v2), pack_bf16(v4, v3)));
        sts128(tab + (136 + lane * 4) * 4, make_uint4(pack_bf16(y1, q), pack_bf16(y2, y1), pack_bf16(y3, y2), pack_bf16(y4, y3)));
      } else if (sub == 1) {
        const uint32_t w22 = pack_bf16(v2, v2);
        sts128(tab + (264 + lane * 8) * 4, make_uint4(pack_bf16(p, p), pack_bf16(v1, p), pack_bf16(v2, v1), w22));
        sts128(tab + (268 + lane * 8) * 4, make_uint4(w22, pack_bf16(v3, v2), pack_bf16(v4, v3), pack_bf16(v4, v4)));
        const uint32_t qq = pack_bf16(e, e);
        const uint32_t k0 = __shfl_sync(~0u, qq, 1), k512 = __shfl_sync(~0u, qq, 2), k1024 = __shfl_sync(~0u, qq, 3);
        if (lane < 8) sts32(tab + lane * 4, lane == 7 ? (k0 & 0xffffu) : 0u);
        sts32(tab + (520 + lane) * 4, lane < 2 ? k512 : lane == 2 ? (k512 & 0xffff0000u) : 0u);
        sts32(tab + (616 + lane) * 4, 0u);
        if (lane < 24) sts32(tab + (712 + lane) * 4, lane == 16 ? k1024 : 0u);
      } else {
        sts64(tab + (552 + lane * 2) * 4, pack_bf16(v1, v2), pack_bf16(v3, v4));
        sts64(tab + (648 + lane * 2) * 4, pack_bf16(y1, y2), pack_bf16(y3, y4));
      }
    }
    mbar_wait(bar(B_XC), 0);
    mbar_wait(bar(B_SC), 0);
    if (tid == 0) TL(8);
    {
      auto norm = [&](uint4 st, int id, int c0, int nc) {
#pragma unroll 1
        for (int it = 0; it < (1 << 20) && !__all_sync(~0u, st.x != 0 && st.y != 0 && st.z != 0 && st.w != 0); it++)
          st = ld_relaxed128(&sy->stat[id * 4]);
        const float r0 = rcp_approx(bf_hi(st.x)), r1 = rcp_approx(bf_hi(st.y)), r2 = rcp_approx(bf_hi(st.z)), r3 = rcp_approx(bf_hi(st.w));
        const float o0 = -bf_lo(st.x) * r0, o1 = -bf_lo(st.y) * r1, o2 = -bf_lo(st.z) * r2, o3 = -bf_lo(st.w) * r3;
        const uint32_t ha = sb + OFF_H + (((id >> 1) & 1) * HP + 8 + (id >> 2)) * 16 + (id & 1) * 8 + c0 * (2 * HP * 16);
        uint2 xv[5], sc[5];
#pragma unroll
        for (int ch = 0; ch < nc; ch++) {
          xv[ch] = lds64(sb + OFF_X1 + (c0 + ch) * XP + id * 8);
          sc[ch] = lds64(sb + OFF_SM + (c0 + ch) * 16);
        }
#pragma unroll
        for (int ch = 0; ch < nc; ch++) {
          const uint32_t n0 = pack_bf16(fmaf(bf_lo(xv[ch].x), r0, o0), fmaf(bf_hi(xv[ch].x), r1, o1));
          const uint32_t n1 = pack_bf16(fmaf(bf_lo(xv[ch].y), r2, o2), fmaf(bf_hi(xv[ch].y), r3, o3));
          sts64(ha + ch * (2 * HP * 16), hfma2_bf16(n0, sc[ch].y, sc[ch].x), hfma2_bf16(n1, sc[ch].y, sc[ch].x));
        }
      };
      if (tid < 80) sts128(sb + OFF_H + ((tid >> 3) * HP + (tid & 7)) * 16, make_uint4(0, 0, 0, 0));
      norm(stw, tid, 0, 5);
      const int xc = (0xF432F1FFF0FFFFFFull >> (4 * warp)) & 15;
      if (xc < 5) norm(stx, 480 + lane, xc, 1);
    }
    named_bar_sync(2, 480);
    if (tid == 0) TL(9);
  }

  bool producer = true;
  if (warp >= 12) {
    asm volatile("setmaxnreg.dec.sync.aligned.u32 " RSIDE ";");
    if (warp == 15) mbar_wait(bar(B_XC), 0), named_bar_sync(9, 64); else if (warp == 14) asm volatile("bar.arrive 9, 64;" ::: "memory");
    mbar_wait_idle<100>(bar(SIDEBAR), 0);
    Sync* sy = &g_sync[lds32v(sb + OFF_PAR)];
    if (warp == 15) {
    if (lane == 0) mbar_arrive(bar(B_PB));
    const uint32_t epoch = lds32v(sb + OFF_PAR);
    if (lane == 0) {
      prefetch_tmap(&tm.wg); prefetch_tmap(&tm.wu); prefetch_tmap(&tm.x1); prefetch_tmap(&tm.wd);
      prefetch_tmap(&tm.res); prefetch_tmap(&tm.out);
    }
    __syncwarp();
    if (lane < 8) {
      Sync* nx = &g_sync[(epoch & 1) ^ 1];
      uint4* p = lane < 6 ? (uint4*)&nx->hhflag[b * 3][0] + lane : (uint4*)&nx->cnt[b & 31][0] + (lane - 6);
      *p = make_uint4(0, 0, 0, 0);
    }
    __syncwarp();
    asm volatile("barrier.cluster.wait.aligned;" ::: "memory");
    if (rank == 0) {
      uint32_t smid;
      asm volatile("mov.u32 %0, %%smid;" : "=r"(smid));
      const int t = smid >> 1;
      int grp = t < 32 ? (t & 7) : t < 60 ? 1 + (t - 32) % 7 : t < 62 ? t - 54 : 8;
      uint32_t tile = 0;
#pragma unroll 1
      for (int i = 0; i < 9; i++) {
        uint32_t tk = 0;
        if (lane == 0) tk = atomicAdd(&sy->cnt[grp][0], 1u);
        tk = __shfl_sync(~0u, tk, 0);
        if (tk < ((grp & 7) ? 8u : 4u)) {
          tile = (grp == 8 ? 4 : grp * 8) + tk;
          break;
        }
        grp = grp == 8 ? 0 : grp + 1;
      }
      if (lane < 2)
        asm volatile("st.async.weak.shared::cluster.mbarrier::complete_tx::bytes.b32 [%0], %1, [%2];"
                     ::"r"(mapa_u32(sb + OFF_TILE, lane)), "r"(tile), "r"(mapa_u32(bar(B_TILE), lane)) : "memory");
    }
    __syncwarp();
    if (b < 96) {
      mbar_wait(bar(B_PRM), 0);
      if (lane == 0) {
        mbar_expect_tx(bar(B_WD), SB2);
        tma_load_3d(sb + 2 * SLOT1, &tm.wd, 0, (b % 24) * 64, (b / 24) * 5, bar(B_WD));
      }
      __syncwarp();
      mbar_wait_idle<100>(bar(B_WD), 0);
      if (lane == 0) {
        bulk_store(g_wdt + b * (SB2 / 2), sb + 2 * SLOT1, SB2);
        bulk_commit();
      }
      __syncwarp();
      bulk_wait_all();
      if (lane == 0) red_relaxed_inc(&sy->cnt[11][0]);
    }
    if (lane == 0) mbar_arrive(bar(B_WFREE));
    __syncwarp();
    mbar_wait_idle<200>(bar(B_WFREE), 0);
    } else {
      if (warp == 14 && lane == 0) mbar_arrive(bar(B_PRM));
      __syncwarp();
        const int lr = lane & 7, lm = lane >> 3;
        float acc[4][4];
#pragma unroll
        for (int i = 0; i < 4; i++)
#pragma unroll
          for (int j = 0; j < 4; j++) acc[i][j] = 0.f;
        const uint32_t wa0 = sb + OFF_W + ((lm >> 1) * 8 + lr) * 64 + (((lm & 1) ^ (lr >> 1)) << 4);
        const int hw = warp - 12;
        const int i0 = (VWSPLIT >> (4 * hw)) & 15, i1 = (VWSPLIT >> (4 * hw + 4)) & 15;
        const uint32_t vec = sb + OFF_VEC + hw * 512;
        const uint32_t va = vec + (lr & 1) * 256 + lm * 16;
        const uint32_t* pm = &sy->modp[0][3 * D_ + i0 * 128 + lane * 4];
        uint4 mp[8];
#pragma unroll
        for (int j = 0; j < 8; j++) mp[j] = make_uint4(0, 0, 0, 0);
        mbar_wait(bar(B_PB), 0);
#pragma unroll 1
        for (int i = i0; i < i1; i++) {
#pragma unroll 1
          for (int it = 0; it < (1 << 20); it++) {
            uint32_t ok = 1u;
#pragma unroll
            for (int j = 0; j < 8; j++) ok &= mp[j].x & mp[j].y & mp[j].z & mp[j].w;
            if (__all_sync(~0u, ok != 0)) break;
#pragma unroll
            for (int j = 0; j < 8; j++) mp[j] = ld_relaxed128(pm + (j >> 2) * D_ + (j & 3) * 6 * D_);
          }
          uint32_t vv[2][2];
#pragma unroll
          for (int k = 0; k < 2; k++) {
            vv[k][0] = pack_bf16(sum4_bf(mp[4 * k].x, mp[4 * k + 1].x, mp[4 * k + 2].x, mp[4 * k + 3].x) + (float)k,
                                 sum4_bf(mp[4 * k].y, mp[4 * k + 1].y, mp[4 * k + 2].y, mp[4 * k + 3].y) + (float)k);
            vv[k][1] = pack_bf16(sum4_bf(mp[4 * k].z, mp[4 * k + 1].z, mp[4 * k + 2].z, mp[4 * k + 3].z) + (float)k,
                                 sum4_bf(mp[4 * k].w, mp[4 * k + 1].w, mp[4 * k + 2].w, mp[4 * k + 3].w) + (float)k);
            sts64(vec + (1 - k) * 256 + lane * 8, vv[k][0], vv[k][1]);
          }
          pm += 128;
          if (i + 1 < i1) {
#pragma unroll
            for (int j = 0; j < 8; j++) mp[j] = ld_relaxed128(pm + (j >> 2) * D_ + (j & 3) * 6 * D_);
          }
#pragma unroll
          for (int j = 0; j < 4; j++) {
            const int d = i * 128 + lane * 4 + j, q = d / 5;
            const uint16_t v = (uint16_t)(vv[1][j >> 1] >> ((j & 1) * 16));
            asm volatile("st.shared.u16 [%0], %1;" ::"r"(sb + OFF_C1 + ((d - q * 5) * 128 + q) * 2), "h"(v) : "memory");
          }
          __syncwarp();
          if (b < 96) {
            mbar_wait(bar(B_W), 0);
#pragma unroll 1
            for (int hf = 0; hf < 2; hf++) {
              const uint32_t wa = wa0 + i * 8192 + hf * 4096;
              uint32_t a[8][4], bb[8];
#pragma unroll
              for (int k = 0; k < 2; k++) ldsm_x4(va + hf * 128 + k * 64, bb[4 * k], bb[4 * k + 1], bb[4 * k + 2], bb[4 * k + 3]);
#pragma unroll
              for (int k = 0; k < 4; k++) {
                ldsm_x4_t_nc(wa + k * 1024, a[2 * k][0], a[2 * k][1], a[2 * k][2], a[2 * k][3]);
                ldsm_x4_t_nc((wa ^ 32) + k * 1024, a[2 * k + 1][0], a[2 * k + 1][1], a[2 * k + 1][2], a[2 * k + 1][3]);
              }
#pragma unroll
              for (int j = 0; j < 8; j++)
                mma_bf16(acc[j & 3][0], acc[j & 3][1], acc[j & 3][2], acc[j & 3][3], a[j][0], a[j][1], a[j][2], a[j][3], bb[j & 6], bb[(j & 6) + 1]);
            }
            __syncwarp();
          }
        }
        if (lane == 0) { mbar_arrive(bar(B_WFREE)); TLM(15); }
        if (b < 96) {
          if (t4 == 0) {
#pragma unroll
            for (int j = 0; j < 4; j++)
              sts64(vec + (j * 8 + g) * 8, __float_as_uint(acc[j >> 1][(j & 1) * 2] + acc[2 + (j >> 1)][(j & 1) * 2]),
                    __float_as_uint(acc[j >> 1][(j & 1) * 2 + 1] + acc[2 + (j >> 1)][(j & 1) * 2 + 1]));
          }
          named_bar_sync(8, 96);
          if (hw == 2) {
            const uint2 p0 = lds64(sb + OFF_VEC + lane * 8), p1 = lds64(sb + OFF_VEC + 512 + lane * 8), p2 = lds64(vec + lane * 8);
            asm volatile("st.relaxed.gpu.global.v2.b32 [%0], {%1, %2};" ::"l"(&sy->vw[0][b * 32 + lane]),
                         "r"(__float_as_uint(__uint_as_float(p0.x) + __uint_as_float(p1.x) + __uint_as_float(p2.x)) | 1u),
                         "r"(__float_as_uint(__uint_as_float(p0.y) + __uint_as_float(p1.y) + __uint_as_float(p2.y)) | 1u) : "memory");
          }
        }
        __syncwarp();
      mbar_wait_idle<100>(bar(B_WFREE), 0);
      asm volatile("barrier.cluster.wait.aligned;" ::: "memory");
    }
    asm volatile("setmaxnreg.dec.sync.aligned.u32 24;");
  } else {
    const int unit = (0x76FF94328510ull >> (4 * warp)) & 15, bch = (BOXMAP >> (4 * warp)) & 15;
    const int H = unit < 5, ch = H ? unit : unit - 5;
#pragma unroll 1
    for (int c = bch; c < 5; c += (warp == BOX2W && c == 0) ? 1 : 8) box_sums(sb, c, lane);
    if (warp == 8) {
      mbar_wait_idle<100>(bar(B_WV + 1), 0);
      if (lane == 0) {
#pragma unroll
        for (int i = B_FULLB; i < B_RES; i++) mbar_init(bar(i), bar_count(i));
        asm volatile("fence.mbarrier_init.release.cluster;" ::: "memory");
        mbar_arrive(bar(B_WFREE));
      }
      __syncwarp();
    }
    if (unit >= 10) mbar_wait_idle<100>(bar(B_WFREE), 0);
    else if (warp == 4) mbar_wait_idle<100>(bar(W4BAR), 0);
    else if (warp == 5) mbar_wait_idle<100>(bar(W5BAR), 0);
    else if (warp == 6) mbar_wait_idle<100>(bar(W6BAR), 0);
    asm volatile("setmaxnreg.inc.sync.aligned.u32 " RCONV ";");
    if (unit < 10) {
      conv_half(sb, ch, H, lane, b);
      if (warp < 3 || warp > 7) publish_x1(sb, &g_sync[lds32v(sb + OFF_PAR)], b, ch, H, lane);
      if (lane == 0) {
        if (warp >= 3 && warp <= 7) mbar_arrive(bar(B_UNIT + warp - 3));
        if (warp == 0) TLM(13);
        if (warp == 2) TL(10);
        if (warp == 11) TL(11);
        if (warp == 3) TL(12);
        if (warp == 4) TLM(16);
        if (warp == 6) TL(20);
        if (warp == 7) TL(23);
      }
      __syncwarp();
    }
    if (warp >= 8) {
      asm volatile("barrier.cluster.wait.aligned;" ::: "memory");
      asm volatile("setmaxnreg.dec.sync.aligned.u32 24;");
    } else {
      producer = false;
    if (warp < 4) mbar_wait_idle<50>(bar(B_CONV), 0);
    asm volatile("setmaxnreg.inc.sync.aligned.u32 232;");
    if (tid == 0) TL(26);
    const int wg = (warp >> 2) ^ rank ^ 1, wq = warp & 3;
    float acc0[64], acc1[64], acc2[64];
#pragma unroll
    for (int i = 0; i < 64; i++) { acc0[i] = 0.f; acc1[i] = 0.f; acc2[i] = 0.f; }
    float s1a = 0.f, s2a = 0.f, s1b = 0.f, s2b = 0.f;
    const int lr = lane & 7, lm = lane >> 3;
    const uint32_t a_off = wg * 4096 + ((lm >> 1) * 8 + lr) * 128 + (((2 * wq + (lm & 1)) ^ lr) << 4);
    const uint32_t c1_addr = sb + OFF_C1 + t4 * 4;
    const uint64_t dB = make_desc(sb + 8192, 12288, 1024, 1);
    uint32_t af[12];

    auto load_a = [&](int slot, int kk, int kstep, uint32_t& o0, uint32_t& o1, uint32_t& o2, uint32_t& o3,
                      uint32_t& ca, uint32_t& cb) {
      ldsm_x4_t(sb + slot * SLOT1 + a_off + kk * 2048, o0, o1, o2, o3);
      ca = lds32(c1_addr + kstep * 32);
      cb = lds32(c1_addr + kstep * 32 + 16);
      k2_stats(o0, s1a, s2a); k2_stats(o2, s1a, s2a);
      k2_stats(o1, s1b, s2b); k2_stats(o3, s1b, s2b);
    };

    mbar_wait(bar(B_WFREE), 0);
    mbar_wait(bar(B_FULL1), 0);
    if (tid == 0) { TLM(27); TLG(44); }
    {
      uint32_t r0, r1, r2, r3, ca, cb;
      load_a(0, 0, 0, r0, r1, r2, r3, ca, cb);
      af[0] = hmul2_bf16(r0, ca); af[1] = hmul2_bf16(r1, ca); af[2] = hmul2_bf16(r2, cb); af[3] = hmul2_bf16(r3, cb);
    }
    int sl = 0, ph = 0;
#pragma unroll 1
    for (int s = 0; s < 19; s++) {
      uint32_t r0, r1, r2, r3, ca, cb;
      const uint64_t d = dB + (uint64_t)((sl * SLOT1) >> 4);
      wg_fence();
      wgmma_rs_n128(acc0, af[0], af[1], af[2], af[3], d, 1);
      wgmma_rs_n128(acc1, af[0], af[1], af[2], af[3], d + 256, 1);
      wgmma_rs_n128(acc2, af[0], af[1], af[2], af[3], d + 512, 1);
      wg_commit();
      load_a(sl, 1, 2 * s + 1, r0, r1, r2, r3, ca, cb);
      wg_wait<1>();
      if (s > 0 && lane == 0) mbar_arrive(bar(B_EMPTY1 + (sl == 0 ? NS1 - 1 : sl - 1)));
      af[4] = hmul2_bf16(r0, ca); af[5] = hmul2_bf16(r1, ca); af[6] = hmul2_bf16(r2, cb); af[7] = hmul2_bf16(r3, cb);
      wg_fence();
      wgmma_rs_n128(acc0, af[4], af[5], af[6], af[7], d + 128, 1);
      wgmma_rs_n128(acc1, af[4], af[5], af[6], af[7], d + 256 + 128, 1);
      wgmma_rs_n128(acc2, af[4], af[5], af[6], af[7], d + 512 + 128, 1);
      wg_commit();
      if (++sl == NS1) { sl = 0; ph ^= 1; }
      mbar_wait(bar(B_FULL1 + sl), ph);
      load_a(sl, 0, 2 * s + 2, r0, r1, r2, r3, ca, cb);
      wg_wait<1>();
      af[0] = hmul2_bf16(r0, ca); af[1] = hmul2_bf16(r1, ca); af[2] = hmul2_bf16(r2, cb); af[3] = hmul2_bf16(r3, cb);
    }
    if ((tid & 127) == 0) TL(28 + wg * 20);
    mbar_wait(bar(B_VW), 0);
    const uint64_t d4 = dB + (uint64_t)((4 * SLOT1) >> 4);
    const uint64_t dX = make_desc(sb + OFF_VW, 3072, 0, 1);
    float rh0, rh1;
    {
      uint32_t r0, r1, r2, r3, ca, cb;
      wg_fence();
      wgmma_rs_n128(acc0, af[0], af[1], af[2], af[3], d4, 1);
      wg_commit();
      load_a(4, 1, 39, r0, r1, r2, r3, ca, cb);
      s1a += __shfl_xor_sync(~0u, s1a, 1); s2a += __shfl_xor_sync(~0u, s2a, 1);
      s1b += __shfl_xor_sync(~0u, s1b, 1); s2b += __shfl_xor_sync(~0u, s2b, 1);
      wg_wait<1>();
      if (lane == 0) mbar_arrive(bar(B_EMPTY1 + 3));
      af[4] = hmul2_bf16(r0, ca); af[5] = hmul2_bf16(r1, ca); af[6] = hmul2_bf16(r2, cb); af[7] = hmul2_bf16(r3, cb);
      wg_fence();
      wgmma_rs_n128(acc0, af[4], af[5], af[6], af[7], d4 + 128, 1);
      wgmma_rs_n128(acc1, af[0], af[1], af[2], af[3], d4 + 256, 1);
      wg_commit();
      s1a += __shfl_xor_sync(~0u, s1a, 2); s2a += __shfl_xor_sync(~0u, s2a, 2);
      s1b += __shfl_xor_sync(~0u, s1b, 2); s2b += __shfl_xor_sync(~0u, s2b, 2);
      const float ma = s1a * (1.f / D_), mb = s1b * (1.f / D_);
      const float va = fmaxf(fmaf(-ma, ma, s2a * (1.f / D_)), 0.f), vb = fmaxf(fmaf(-mb, mb, s2b * (1.f / D_)), 0.f);
      const float da = sqrt_approx(bf_round(bf_round(va) + 1e-5f)), db = sqrt_approx(bf_round(bf_round(vb) + 1e-5f));
      const uint32_t da2 = pack_bf16(da, da), db2 = pack_bf16(db, db);
      af[8] = t4 == 0 ? pack_bf16(-ma, -ma) : t4 == 1 ? da2 : 0u;
      af[9] = t4 == 0 ? pack_bf16(-mb, -mb) : t4 == 1 ? db2 : 0u;
      af[10] = lds32v(sb + OFF_ZERO); af[11] = lds32v(sb + OFF_ZERO);
      rh0 = 0.5f * rcp_approx(bf_lo(da2)); rh1 = 0.5f * rcp_approx(bf_lo(db2));
      wg_fence();
      wgmma_rs_n128(acc0, af[8], af[9], af[10], af[11], dX, 1);
      wg_commit();
    }
    wgmma_rs_n128(acc1, af[4], af[5], af[6], af[7], d4 + 256 + 128, 1);
    wgmma_rs_n128(acc1, af[8], af[9], af[10], af[11], dX + 64, 1);
    wg_commit();
    float o[80];
    const uint32_t stg_row = wg * 64 + wq * 16 + (lm & 1) * 8 + lr;
    const uint32_t stg_addr = sb + OFF_STG + stg_row * 128 + (((lm >> 1) ^ lr) << 4);
    const uint64_t dW = make_desc(sb, 4096, 512, 2);
    const uint64_t dS = make_desc(sb + OFF_STG + wg * 8192, 16, 1024, 1);
    auto publish = [&](int c) {
      fence_async_smem();
      __syncwarp();
      if (lane == 0) mbar_arrive(bar(B_STG + 3 * wg + c));
    };
    wg_wait<1>();
    if ((tid & 127) == 0) TL(29 + wg * 20);
    k2_glu_half<0>(acc0, stg_addr, rh0, rh1);
    wg_fence();
    wgmma_rs_n128(acc2, af[0], af[1], af[2], af[3], d4 + 512, 1);
    wgmma_rs_n128(acc2, af[4], af[5], af[6], af[7], d4 + 512 + 128, 1);
    wgmma_rs_n128(acc2, af[8], af[9], af[10], af[11], dX + 128, 1);
    wg_commit();
    k2_glu_half<1>(acc0, stg_addr, rh0, rh1);
    publish(0);
    if ((tid & 127) == 0) TL(30 + wg * 20);
    wg_wait<1>();
    k2_glu_half<0>(acc1, stg_addr + 16384, rh0, rh1);
    mbar_wait(bar(B_FULLB + 0), 0);
    named_bar_sync(2 + wg, 128);
    wg_wait<0>();
    if (lane == 0) mbar_arrive(bar(B_EMPTY1 + 4));
#pragma unroll
    for (int i = 0; i < 80; i++) o[i] = 0.f;
    wg_fence();
#pragma unroll
    for (int q = 0; q < 4; q++) wgmma_ss_n160(o, dS + q * 2, dW + q * 64, q != 0);
    wg_commit();
    k2_glu_half<1>(acc1, stg_addr + 16384, rh0, rh1);
    publish(1);
    if ((tid & 127) == 0) TL(31 + wg * 20);
    mbar_wait(bar(B_FULLB + 1), 0);
    named_bar_sync(2 + wg, 128);
    wg_fence();
#pragma unroll
    for (int q = 0; q < 4; q++) wgmma_ss_n160(o, dS + 1024 + q * 2, dW + (SB2 >> 4) + q * 64, 1);
    wg_commit();
    wg_wait<1>();
    if (lane == 0) mbar_arrive(bar(B_DRAIN + 8 * wg + 0));
    if ((tid & 127) == 0) TL(32 + wg * 20);
    k2_glu_half<0>(acc2, stg_addr + 32768, rh0, rh1);
    k2_glu_half<1>(acc2, stg_addr + 32768, rh0, rh1);
    publish(2);
    if ((tid & 127) == 0) TL(33 + wg * 20);
    mbar_wait(bar(B_FULLB + 2), 0);
    named_bar_sync(2 + wg, 128);
    wg_fence();
#pragma unroll
    for (int q = 0; q < 4; q++) wgmma_ss_n160(o, dS + 2048 + q * 2, dW + 2 * (SB2 >> 4) + q * 64, 1);
    wg_commit();
    wg_wait<1>();
    if (lane == 0) mbar_arrive(bar(B_DRAIN + 8 * wg + 1));
    wg_wait<0>();
    if (lane == 0) mbar_arrive(bar(B_DRAIN + 8 * wg + 2));
    asm volatile("barrier.cluster.wait.aligned;" ::: "memory");
    const bool keep = (wg == rank);
    const uint64_t dA = make_desc(sb + OFF_A2 + wg * 8192, 16, 1024, 1);
    {
      int sb2 = 3;
      bool ready = false;
#pragma unroll 1
      for (int q = 3; q < 12; q++) {
        const bool pause = q == 12 - SKEW && keep;
        if (pause) {
          if (SKEW > 3) {
            wg_wait<0>();
            if (lane == 0) mbar_arrive(bar(B_DRAIN + 8 * wg + q - 1));
          }
          named_bar_sync(1, 256);
        }
        if (!ready) {
          mbar_wait(bar(B_FULLB + q), 0);
          mbar_wait(bar(B_FULLA + 9 * wg + q - 3), 0);
        }
        const uint32_t p0 = mbar_test(bar(B_FULLB + q + 1), 0), p1 = mbar_test(bar(B_FULLA + 9 * wg + q - 2), 0);
        if ((tid & 127) == 0) TL(keep ? 61 + q : 76 + q);
        const uint64_t da = dA + (uint64_t)((((q - 3) & 3) * SA2) >> 4), db = dW + (uint64_t)((sb2 * SB2) >> 4);
        wg_fence();
#pragma unroll
        for (int k = 0; k < 4; k++) wgmma_ss_n160(o, da + k * 2, db + k * 64, 1);
        wg_commit();
        ready = __all_sync(~0u, p0 & p1);
        if (q < 9 && q > 3 && !pause) {
          wg_wait<1>();
          if (lane == 0) mbar_arrive(bar(B_DRAIN + 8 * wg + q - 1));
        }
        if (++sb2 == NB2) sb2 = 0;
      }
    }
    const int t128 = tid & 127;
    if (!keep) {
      if (SKEW) asm volatile("bar.arrive 1, 256;" ::: "memory");
      mbar_wait_cluster(bar(B_PEER), 0);
      const uint32_t rdst = mapa_u32(sb + OFF_RECV + t128 * 16, rank ^ 1);
      const uint32_t rbar = mapa_u32(bar(B_RECV), rank ^ 1);
      wg_wait<0>();
      if (t128 == 0) TL(42);
#pragma unroll
      for (int i = 0; i < 10; i++)
        asm volatile("st.async.weak.shared::cluster.mbarrier::complete_tx::bytes.v4.b32 [%0], {%1,%2,%3,%4}, [%5];"
                     ::"r"(rdst + i * 2048), "r"(pack_bf16(o[8 * i], o[8 * i + 1])), "r"(pack_bf16(o[8 * i + 2], o[8 * i + 3])),
                     "r"(pack_bf16(o[8 * i + 4], o[8 * i + 5])), "r"(pack_bf16(o[8 * i + 6], o[8 * i + 7])), "r"(rbar) : "memory");
      if (t128 == 0) TL(43);
      asm volatile("barrier.cluster.arrive.relaxed.aligned;" ::: "memory");
    } else {
      uint32_t xr[40], gv[20];
      const uint32_t res_addr = sb + OFF_RES + ((lm >> 1) * 8 + lr) * 128 + (((2 * wq + (lm & 1)) ^ lr) << 4);
      mbar_wait(bar(B_RES), 0);
#pragma unroll
      for (int i = 0; i < 10; i++) ldsm_x4_t(res_addr + i * 2048, xr[4 * i], xr[4 * i + 1], xr[4 * i + 2], xr[4 * i + 3]);
#pragma unroll
      for (int i = 0; i < 5; i++) ldsm_x4(sb + OFF_GB + i * 64 + lm * 16, gv[4 * i], gv[4 * i + 1], gv[4 * i + 2], gv[4 * i + 3]);
      const int tile = lds32(sb + OFF_TILE);
      mbar_wait(bar(B_DRAIN + 7), 0);
      mbar_wait(bar(B_DRAIN + 8 + 7), 0);
      mbar_wait_cluster(bar(B_RECV), 0);
      asm volatile("barrier.cluster.arrive.relaxed.aligned;" ::: "memory");
      if (t128 == 0) TL(36);
      uint4 p[10];
#pragma unroll
      for (int i = 0; i < 10; i++) p[i] = lds128(sb + OFF_RECV + t128 * 16 + i * 2048);
      wg_wait<0>();
      if (t128 == 0) TL(35);
      const int orow = (lm & 1) * 8 + lr;
      const uint32_t out_base = sb + OFF_OUT + wq * 5120;
      const uint32_t oa0 = out_base + orow * 64 + (((lm >> 1) ^ ((orow >> 1) & 3)) << 4);
#pragma unroll
      for (int i = 0; i < 10; i++) {
        const int a = 8 * i;
        const uint32_t y0 = hfma2_bf16(gv[2 * i], hadd2_bf16(pack_bf16(o[a + 0], o[a + 1]), p[i].x), xr[4 * i]);
        const uint32_t y1 = hfma2_bf16(gv[2 * i], hadd2_bf16(pack_bf16(o[a + 2], o[a + 3]), p[i].y), xr[4 * i + 1]);
        const uint32_t y2 = hfma2_bf16(gv[2 * i + 1], hadd2_bf16(pack_bf16(o[a + 4], o[a + 5]), p[i].z), xr[4 * i + 2]);
        const uint32_t y3 = hfma2_bf16(gv[2 * i + 1], hadd2_bf16(pack_bf16(o[a + 6], o[a + 7]), p[i].w), xr[4 * i + 3]);
        stsm_x4_nc(((i & 1) ? (oa0 ^ 32) : oa0) + (i >> 1) * 1024, y0, y1, y2, y3);
      }
      fence_async_smem();
      __syncwarp();
      if (lane == 0) {
        tma_store_3d(&tm.out, out_base, 0, (tile >> 2) * 128 + wg * 64 + wq * 16, (tile & 3) * 5);
        bulk_commit();
        if (b == 0 && wq == 0) atomicAdd(&g_epoch, 1u);
      }
      __syncwarp();
      bulk_wait_read();
      if (t128 == 0) { TLM(37); TLG(47); }
      __syncwarp();
    }
    }
  }

  if (producer) {
    Sync* sy = &g_sync[lds32v(sb + OFF_PAR)];
    mbar_wait(bar(B_WFREE), 0);
    mbar_wait_cluster(bar(B_TILE), 0);
    const int tile = lds32(sb + OFF_TILE);
    const int rb = tile >> 2, jn = tile & 3, jf = 4 * rank + jn, t0 = rb * 128;
#define SRC(i) ((i) + ((i) >= jn))
    if (warp == 8) {
      int sl = 0, ph = 1;
      mbar_wait(bar(B_WFREE), 0);
#pragma unroll 1
      for (int s = 0; s < 20; s++) {
        const uint32_t slot = sb + sl * SLOT1, fb = bar(B_FULL1 + sl);
        if (s == 3) {
          uint32_t n = 0;
#pragma unroll 1
          for (int it = 0; it < (1 << 20) && __shfl_sync(~0u, n, 0) < 96u; it++) n = ld_relaxed(&sy->cnt[11][0]);
          mbar_wait_idle<100>(bar(B_CONV), 0);
        }
        if (s >= NS1) mbar_wait(bar(B_EMPTY1 + sl), ph);
        if (lane == 0) {
          mbar_expect_tx(fb, 24576);
          tma_load_4d(slot + 8192, &tm.wg, 0, (s & 3) * 32, jf * 3, s >> 2, fb);
          tma_load_4d(slot + 20480, &tm.wu, 0, (s & 3) * 32, jf * 3, s >> 2, fb);
        }
        __syncwarp();
        if (++sl == NS1) { sl = 0; ph ^= 1; }
      }
#pragma unroll 1
      for (int q = 0; q < 12; q++) {
        if (q >= NB2) { mbar_wait(bar(B_DRAIN + q - NB2), 0); mbar_wait(bar(B_DRAIN + 8 + q - NB2), 0); }
        else if (q != 2 && q != 5) mbar_wait(bar(B_EMPTY1 + (q < 2 ? q : q < 5 ? q - 1 : 4)), 1);
        const int src = (q < 3) ? jn : SRC((q - 3) % 3);
        const int ch = (q < 3) ? q : (q - 3) / 3;
        if (lane == 0) {
          mbar_expect_tx(bar(B_FULLB + q), SB2);
          bulk_load(sb + (q >= NB2 ? q - NB2 : q) * SB2, g_wdt + (jn * 24 + (4 * rank + src) * 3 + ch) * (SB2 / 2), SB2, bar(B_FULLB + q));
          TL(88 + q);
        }
        __syncwarp();
      }
      mbar_wait(bar(B_DRAIN + 5), 0);
      mbar_wait(bar(B_DRAIN + 8 + 5), 0);
      if (lane == 0) {
        mbar_expect_tx(bar(B_RES), 20480);
        tma_load_3d(sb + OFF_RES, &tm.res, t0 + rank * 64, 0, jn * 32, bar(B_RES));
      }
      __syncwarp();
      mbar_wait(bar(B_DRAIN + 6), 0);
      mbar_wait(bar(B_DRAIN + 8 + 6), 0);
      if (lane == 0) mbar_arrive_remote(mapa_u32(bar(B_PEER), rank ^ 1));
    } else if (warp == 9) {
      int sl = 0, ph = 1;
      const uint32_t* fl = &sy->cnt[16 + (rb & 8) + min(lane, 4)][0];
      uint32_t f = ld_relaxed(fl);
      mbar_wait(bar(B_WFREE), 0);
#pragma unroll 1
      for (int s = 0; s < 20; s++) {
#pragma unroll 1
        for (int it = 0; it < (1 << 20) && __shfl_sync(~0u, f, s >> 2) < 128u; it++) f = ld_relaxed(fl);
        if (lane == 0 && (s & 3) == 0) TLM(100 + (s >> 2));
        if (s == 3) mbar_wait_idle<100>(bar(B_CONV), 0);
        if (s >= NS1) mbar_wait(bar(B_EMPTY1 + sl), ph);
        if (lane == 0) {
          mbar_expect_tx(bar(B_FULL1 + sl), 8192);
          tma_load_3d(sb + sl * SLOT1, &tm.x1, 0, s * 32, rb * 2, bar(B_FULL1 + sl));
        }
        __syncwarp();
        if (++sl == NS1) { sl = 0; ph ^= 1; }
      }
    } else if (warp >= 13) {
#pragma unroll 1
      for (int H = (warp == 15); H < 2; H++) {
        mbar_wait_idle<150>(bar(B_UNIT + (H ? warp - 12 : warp == 13 ? 0 : 4)), 0);
        publish_x1(sb, sy, b, warp - 10 - H, H, lane);
      }
      if (warp == 13) {
#pragma unroll 1
        for (int i = 0; i < 5; i++) {
          asm volatile("st.shared.u16 [%0], %1;" ::"r"(sb + OFF_GB + (i * 32 + lane) * 2),
                       "h"((uint16_t)(__float_as_uint(poll_mod(&sy->modp[0][5 * D_ + jn * 160 + i * 32 + lane])) >> 16)) : "memory");
        }
        __syncwarp();
        if (lane == 0) mbar_arrive(bar(B_RES));
      } else if (warp == 14) {
        mbar_wait(bar(B_CONV), 0);
#pragma unroll 1
        for (int i = 0; i < 6; i++) {
          uint4 w = make_uint4(0, 0, 0, 0);
#pragma unroll 1
          for (int it = 0; it < (1 << 20) && !__all_sync(~0u, (w.x & w.y & w.z & w.w & 1u) != 0); it++) {
            const uint2* p = &sy->vw[0][jf * 192 + i * 32 + lane];
            asm volatile("ld.relaxed.gpu.global.v2.b32 {%0,%1}, [%2];" : "=r"(w.x), "=r"(w.y) : "l"(p) : "memory");
            asm volatile("ld.relaxed.gpu.global.v2.b32 {%0,%1}, [%2];" : "=r"(w.z), "=r"(w.w) : "l"(p + F_) : "memory");
          }
          sts128(sb + OFF_VW + i * 1024 + 512 + lane * 16, make_uint4(0, 0, 0, 0));
          const int col = (i & 1) * 32 + lane;
          const uint32_t ea = sb + OFF_VW + (i >> 1) * 1024 + (col & 7) * 2;
#pragma unroll
          for (int k = 0; k < 4; k++) {
            const float v = __uint_as_float(k == 0 ? w.x : k == 1 ? w.y : k == 2 ? w.z : w.w);
            const float hi = bf_round(v);
            const uint32_t hl = pack_bf16(hi, v - hi);
            const int r = (k & 1) * 2;
            const uint32_t ad = ea + (k >> 1) * 3072 + r * 128;
            asm volatile("st.shared.u16 [%0], %1;" ::"r"(ad + (((col >> 3) ^ r) << 4)), "h"((uint16_t)hl) : "memory");
            asm volatile("st.shared.u16 [%0], %1;" ::"r"(ad + 128 + (((col >> 3) ^ (r + 1)) << 4)), "h"((uint16_t)(hl >> 16)) : "memory");
          }
        }
        fence_async_smem();
        __syncwarp();
        if (lane == 0) mbar_arrive(bar(B_VW));
      }
    }
    if (warp >= 10) {
      const int w = warp >= 13, c = warp - 10 - 3 * w;
      __nv_bfloat16* img = g_hh + (size_t)((rb * 2 + w) * 24 + rank * 12 + c) * 4096;
      const uint32_t* fl = &sy->hhflag[(rb * 8 + 4 * rank + SRC(min(lane, 2))) * 3 + c][w];
      uint32_t f = ld_relaxed(fl);
      mbar_wait_idle<200>(bar(B_FULLB), 0);
      mbar_wait(bar(B_STG + 3 * w + c), 0);
      if (HOLD_Q >= 0 && c == 2) mbar_wait(bar(B_HOLD + w), 0);
      if (lane == 0) {
        if (c == 0 && w != rank) TLM(41);
        bulk_store(img + jn * (3 * 4096), sb + OFF_STG + c * 16384 + w * 8192, 8192);
        bulk_commit();
      }
      __syncwarp();
      bulk_wait_all();
      if (lane == 0) {
        st_relaxed(&sy->hhflag[(rb * 8 + jf) * 3 + c][w], 1u);
        if (c == 0 && w != rank) TL(38);
        mbar_arrive(bar(B_DRAIN + 8 * w + c));
      }
      __syncwarp();
#pragma unroll 1
      for (int i = 0; i < 3; i++) {
        const int q = 3 * c + i;
#pragma unroll 1
        for (int it = 0; it < (1 << 20) && __shfl_sync(~0u, f, i) == 0; it++) f = ld_relaxed(fl);
        if (q >= 1) mbar_wait(bar(B_DRAIN + 8 * w + q - 1), 0);
        else mbar_wait(bar(B_EMPTY1 + 4), 1);
        if (lane == 0) {
          mbar_expect_tx(bar(B_FULLA + 9 * w + q), 8192);
          bulk_load(sb + OFF_A2 + (q & 3) * SA2 + w * 8192, img + SRC(i) * (3 * 4096), 8192, bar(B_FULLA + 9 * w + q));
          if (w != rank) TL(109 + q);
          if (q == HOLD_Q) mbar_arrive(bar(B_HOLD + w));
        }
        __syncwarp();
      }
    }
    __syncwarp();
    asm volatile("barrier.cluster.arrive.relaxed.aligned;" ::: "memory");
  }
  asm volatile("barrier.cluster.wait.aligned;" ::: "memory");
  TL_DUMP(0, 128);
}
typedef CUresult (*EncodeFn)(CUtensorMap*, CUtensorMapDataType, cuuint32_t, void*, const cuuint64_t*, const cuuint64_t*,
                             const cuuint32_t*, const cuuint32_t*, CUtensorMapInterleave, CUtensorMapSwizzle,
                             CUtensorMapL2promotion, CUtensorMapFloatOOBfill);

static void make_map(EncodeFn enc, CUtensorMap* m, void* base, int rank, const cuuint64_t* dims, const cuuint64_t* strides,
                     const cuuint32_t* box, CUtensorMapSwizzle swz) {
  cuuint32_t es[4] = {1, 1, 1, 1};
  CUresult r = enc(m, CU_TENSOR_MAP_DATA_TYPE_BFLOAT16, rank, base, dims, strides, box, es, CU_TENSOR_MAP_INTERLEAVE_NONE,
                   swz, CU_TENSOR_MAP_L2_PROMOTION_L2_128B, CU_TENSOR_MAP_FLOAT_OOB_FILL_NONE);
  if (r != CUDA_SUCCESS) fprintf(stderr, "cuTensorMapEncodeTiled failed: %d\n", (int)r);
}

extern "C" void kernel_launch(void* const* d_in, const int* in_sizes, int n_in, void* d_out, int out_size) {
  (void)in_sizes; (void)n_in; (void)out_size;
  static EncodeFn enc = nullptr;
  static void *p_x1T = nullptr, *p_xT = nullptr;
  if (!enc) {
    cudaDriverEntryPointQueryResult qr;
    void* fn = nullptr;
    cudaGetDriverEntryPoint("cuTensorMapEncodeTiled", &fn, cudaEnableDefault, &qr);
    enc = (EncodeFn)fn;
    cudaGetSymbolAddress(&p_x1T, g_x1T);
    cudaGetSymbolAddress(&p_xT, g_xT);
    cudaFuncSetAttribute(fused_kernel, cudaFuncAttributeMaxDynamicSharedMemorySize, SMEM);
  }
  const CUtensorMapSwizzle S64 = CU_TENSOR_MAP_SWIZZLE_64B, S128 = CU_TENSOR_MAP_SWIZZLE_128B;
  Maps tm;
  {
    cuuint64_t dx[3] = {32, L_, D_ / 32}, dw[3] = {32, F_, D_ / 32}, st[2] = {D_ * 2, 64};
    cuuint32_t b64[3] = {32, 64, 5}, b16[3] = {32, 16, 5};
    make_map(enc, &tm.xi, d_in[0], 3, dx, st, b64, S64);
    make_map(enc, &tm.wd, d_in[10], 3, dw, st, b64, S64);
    make_map(enc, &tm.out, d_out, 3, dx, st, b16, S64);
  }
  {
    cuuint64_t d2[2] = {L_, D_}, s2[1] = {L_ * 2};
    cuuint32_t b2[2] = {64, 160};
    make_map(enc, &tm.xo, p_xT, 2, d2, s2, b2, S128);
    cuuint64_t d3[3] = {64, D_, L_ / 64}, s3[2] = {L_ * 2, 128};
    cuuint32_t b3[3] = {64, 32, 2};
    make_map(enc, &tm.x1, p_x1T, 3, d3, s3, b3, S128);
    cuuint64_t dr[3] = {L_, 5, 128}, sr[2] = {128 * L_ * 2, L_ * 2};
    cuuint32_t br[3] = {64, 5, 32};
    make_map(enc, &tm.res, p_x1T, 3, dr, sr, br, S128);
  }
  {
    cuuint64_t dw[2] = {F_, D_}, sw[1] = {F_ * 2}, dm[2] = {6 * D_, D_}, sm[1] = {6 * D_ * 2};
    cuuint32_t b32[2] = {32, 160}, ba[2] = {64, 128}, bb[2] = {64, 32};
    make_map(enc, &tm.wgc, d_in[8], 2, dw, sw, b32, S64);
    make_map(enc, &tm.wuc, d_in[9], 2, dw, sw, b32, S64);
    make_map(enc, &tm.wma, d_in[12], 2, dm, sm, ba, S128);
    make_map(enc, &tm.wmb, d_in[12], 2, dm, sm, bb, S128);
  }
  {
    cuuint64_t d4[4] = {64, 128, F_ / 64, 5}, s4[3] = {5 * F_ * 2, 128, F_ * 2};
    cuuint32_t b4[4] = {64, 32, 3, 1};
    make_map(enc, &tm.wg, d_in[8], 4, d4, s4, b4, S128);
    make_map(enc, &tm.wu, d_in[9], 4, d4, s4, b4, S128);
  }
  typedef const __nv_bfloat16* P;
  fused_kernel<<<128, 512, SMEM, cudaStreamPerThread>>>((P)d_in[0], (P)d_in[1], (P)d_in[2], (P)d_in[3], (P)d_in[4], (P)d_in[5],
                                                        (P)d_in[6], (P)d_in[11], tm);
}
```
